```python
import torch

def _softmax(x, axis=-1):
    return torch.softmax(x, dim=axis)
def _gelu(x):
    return torch.nn.functional.gelu(x, approximate="tanh")
def _silu(x):
    return torch.nn.functional.silu(x)
def _sigmoid(x):
    return torch.sigmoid(x)
def _layernorm(x, axis=-1, eps=1e-5):
    m = x.mean(dim=axis, keepdim=True)
    v = x.var(dim=axis, keepdim=True, unbiased=False)
    return (x - m) / torch.sqrt(v + eps)
def _scatter_add(tgt, idx, src, axis=0):
    return tgt.clone().index_add_(axis, idx, src)
def _segment_sum(src, seg, n):
    out = torch.zeros((n,) + src.shape[1:], dtype=src.dtype)
    return out.index_add_(0, seg, src)
def _pad(x, pw):
    flat = tuple(v for pair in reversed(pw) for v in pair)
    return torch.nn.functional.pad(x, flat)

kernel_name = 'recurrent_scan__linear_kernel_hedgehog__mixer_token_mlp__prompt'

def setup_inputs():

    _w = (lambda a: (lambda t: t.to(torch.bfloat16) if t.is_floating_point() else t)(torch.as_tensor(a)))
    def _A_setup():
        B, S, D, H = 1, 2048, 576, 32
        Dh = D // H
        return {
            "x": _w((lambda *s: torch.randn(*s, dtype=torch.bfloat16) * 0.05)(B, S, D)),
            "wqkv": _w((lambda *s: torch.randn(*s, dtype=torch.bfloat16) * 0.4)(D, 3 * D)),
            "w_phi": _w((lambda *s: torch.randn(*s, dtype=torch.bfloat16) * 0.4)(H, Dh, Dh) * (Dh ** -0.5)),
            "wo": _w((lambda *s: torch.randn(*s, dtype=torch.bfloat16) * 0.2)(D, D)),
        }
    _A_in = _A_setup()

    def _B_setup():
        B, S, D, F = 1, 2048, 576, 4608
        return {
            "x": _w((lambda *s: torch.randn(*s, dtype=torch.bfloat16) * 0.05)(B, S, D)),
            "w1": _w((lambda *s: torch.randn(*s, dtype=torch.bfloat16) * 0.4)(S, F) * (S ** -0.5)),
            "b1": _w((lambda *s: torch.randn(*s, dtype=torch.bfloat16) * 3.2)(F) * 0.02),
            "w2": _w((lambda *s: torch.randn(*s, dtype=torch.bfloat16) * 0.1)(F, S) * (F ** -0.5)),
            "b2": _w((lambda *s: torch.randn(*s, dtype=torch.bfloat16) * 0.2)(S) * 0.02),
        }
    _B_in = _B_setup()

    return {
        "A_x": _A_in["x"],
        "A_wqkv": _A_in["wqkv"],
        "A_w_phi": _A_in["w_phi"],
        "A_wo": _A_in["wo"],
        "B_x": _B_in["x"],
        "B_w1": _B_in["w1"],
        "B_b1": _B_in["b1"],
        "B_w2": _B_in["w2"],
        "B_b2": _B_in["b2"],
    }

def reference(A_x, A_wqkv, A_w_phi, A_wo, B_x, B_w1, B_b1, B_w2, B_b2):
    def _A_ref(x, wqkv, w_phi, wo):
        B, S, D = x.shape
        H = 32; Dh = D // H
        qkv = (lambda x, *d: x.permute(*d))((x @ wqkv).reshape(B, S, 3, H, Dh), 2, 0, 3, 1, 4)
        q, k, v = qkv[0], qkv[1], qkv[2]
        pq = torch.einsum("bhsd,hdf->bhsf", q, w_phi)
        pk = torch.einsum("bhsd,hdf->bhsf", k, w_phi)
        phi_q = torch.concatenate([_softmax(pq, axis=-1), _softmax(-pq, axis=-1)], axis=-1)
        phi_k = torch.concatenate([_softmax(pk, axis=-1), _softmax(-pk, axis=-1)], axis=-1)
        kv = torch.einsum("bhsf,bhsd->bhfd", phi_k, v)
        z  = torch.einsum("bhsf->bhf", phi_k)
        num = torch.einsum("bhqf,bhfd->bhqd", phi_q, kv)
        den = torch.einsum("bhqf,bhf->bhq", phi_q, z)[..., None] + 1e-6
        o = num / den
        return (lambda x, *d: x.permute(*d))(o, 0, 2, 1, 3).reshape(B, S, D) @ wo

    def _B_ref(x, w1, b1, w2, b2):
        B, S, D = x.shape
        h = _layernorm(x, axis=-1)
        u = torch.einsum("bsd,sf->bdf", h, w1) + b1
        u = _gelu(u)
        y = torch.einsum("bdf,fs->bds", u, w2) + b2
        return (lambda x, *d: x.permute(*d))(y, 0, 2, 1)

    x = A_x
    xn = _layernorm(x, axis=-1)
    s = _A_ref(xn, A_wqkv, A_w_phi, A_wo)
    g = _silu(_B_ref(xn, B_w1, B_b1, B_w2, B_b2))
    return x + s * g
```

```cpp
#include <cuda_runtime.h>
#include <cuda_bf16.h>
#include <cuda.h>
#include <stdint.h>

namespace hk {

typedef __nv_bfloat16 bf16;

constexpr int SEQ = 2048, DM = 576, FF = 4608;
constexpr int NCTA = 132;
constexpr int N_G1 = 108;
constexpr int N_G2 = 96;
constexpr int MST = 5;
constexpr int M_A = 16384, M_B = 24576, M_STAGE = M_A + M_B;
#define HK_FST 4
constexpr int FST = HK_FST;
constexpr int F_A = 16384, F_B = 18432, F_SLOT = F_A + F_B;
constexpr int KVB_BYTES = 23040;
constexpr int EBUF = 2 * KVB_BYTES;
constexpr int EBUF_OFF = 4 * F_SLOT;
constexpr int FOLD_OFF = MST * M_STAGE;
constexpr int FOLD_TILE = 144 * 144;
constexpr int FOLD_PHI = 4 * 324 * 2;
constexpr int BARS_OFF = EBUF_OFF + 2 * EBUF;
constexpr int SMEM_BYTES = BARS_OFF + 1024;
constexpr int KV_CH = 1056;
constexpr int N_ROLES = 132 * 4;
constexpr int N_JOBS = 192;
constexpr int KVP_BYTES = 4 * 36 * 20 * 4;
static_assert(FOLD_OFF + FOLD_TILE + FOLD_PHI <= BARS_OFF, "smem layout");

enum { C_LN = 0, C_FOLD = 1, C_JOB = 2, C_DONE = 3, C_U = 4  , C_KV = 16  , C_KVB = 24  ,
       C_O = 32  , C_X = 96  ,
       C_LNK = 288  , C_NUM = 320 };
#define HK_LAYOUT 0
constexpr size_t SZ_XN = 16 * 9 * 16384;
constexpr size_t SZ_H = 32 * 3 * 24576;
constexpr size_t SZ_U = 3 * 72 * 24576;
constexpr size_t SZ_WKV = 8 * 9 * 18432;
constexpr size_t SZ_WQ = 4 * 9 * 18432;
constexpr size_t SZ_WO = 6 * 9 * 12288;
constexpr size_t SZ_O = 16 * 9 * 16384;
constexpr size_t SZ_KVB = 8 * KVB_BYTES;
constexpr size_t SZ_KVS = 32 * 36 * 20 * 4;
constexpr size_t SZ_XCH = 96 * 2 * 24576;
constexpr size_t SZ_CNT = C_NUM * 128;
constexpr size_t O_CNT = 0, O_KVS = O_CNT + SZ_CNT, O_KVB = O_KVS + SZ_KVS, O_WQ = O_KVB + SZ_KVB, O_WKV = O_WQ + SZ_WQ, O_XN = O_WKV + SZ_WKV,
                 O_H = O_XN + SZ_XN, O_WO = O_H + SZ_H, O_O = O_WO + SZ_WO, O_U = O_O + SZ_O, O_XCH = O_U + SZ_U, O_END = O_XCH + SZ_XCH;
__device__ __align__(1024) uint8_t g_scratch[O_END];
#define g_xn_img (g_scratch + O_XN)
#define g_h_img (g_scratch + O_H)
#define g_u_img (g_scratch + O_U)
#define g_wkv_img (g_scratch + O_WKV)
#define g_wq_img (g_scratch + O_WQ)
#define g_wo_img (g_scratch + O_WO)
#define g_o_img (g_scratch + O_O)
#define g_kvb_img (g_scratch + O_KVB)
#define g_xch (g_scratch + O_XCH)
#define g_kvsum (reinterpret_cast<float*>(g_scratch + O_KVS))
#define g_cnt (reinterpret_cast<unsigned*>(g_scratch + O_CNT))

__device__ __forceinline__ uint32_t smem_u32(const void* p) { return (uint32_t)__cvta_generic_to_shared(p); }
__device__ __forceinline__ void mbar_init(uint32_t bar, uint32_t cnt) {
  asm volatile("mbarrier.init.shared::cta.b64 [%0], %1;" ::"r"(bar), "r"(cnt) : "memory");
}
__device__ __forceinline__ void mbar_expect_tx(uint32_t bar, uint32_t bytes) {
  asm volatile("mbarrier.arrive.expect_tx.shared::cta.b64 _, [%0], %1;" ::"r"(bar), "r"(bytes) : "memory");
}
__device__ __forceinline__ void mbar_arrive(uint32_t bar) {
  asm volatile("mbarrier.arrive.shared::cta.b64 _, [%0];" ::"r"(bar) : "memory");
}
__device__ __forceinline__ uint32_t mapa(uint32_t addr, uint32_t cta) {
  uint32_t r;
  asm volatile("mapa.shared::cluster.u32 %0, %1, %2;" : "=r"(r) : "r"(addr), "r"(cta));
  return r;
}
__device__ __forceinline__ void mbar_arrive_remote(uint32_t remote_bar) {
  asm volatile("mbarrier.arrive.release.cluster.shared::cluster.b64 _, [%0];" ::"r"(remote_bar) : "memory");
}
__device__ __forceinline__ void mbar_wait(uint32_t bar, uint32_t parity) {
  asm volatile(
      "{\n.reg .pred p, q;\n.reg .u32 n;\nmov.u32 n, 0;\n"
      "LAB_WAIT:\nmbarrier.try_wait.parity.shared::cta.b64 p, [%0], %1;\n@p bra DONE;\n"
      "add.u32 n, n, 1;\nsetp.lt.u32 q, n, 4194304;\n@q bra LAB_WAIT;\ntrap;\nDONE:\n}" ::"r"(bar),
      "r"(parity)
      : "memory");
}
__device__ __forceinline__ void mbar_wait_cluster(uint32_t bar, uint32_t parity) {
  asm volatile(
      "{\n.reg .pred p, q;\n.reg .u32 n;\nmov.u32 n, 0;\n"
      "LAB_WAIT:\nmbarrier.try_wait.parity.acquire.cluster.shared::cta.b64 p, [%0], %1;\n@p bra DONE;\n"
      "add.u32 n, n, 1;\nsetp.lt.u32 q, n, 4194304;\n@q bra LAB_WAIT;\ntrap;\nDONE:\n}" ::"r"(bar),
      "r"(parity)
      : "memory");
}
__device__ __forceinline__ void flag_wait(const unsigned* p, unsigned target) {
  asm volatile(
      "{\n.reg .pred p, q;\n.reg .u32 n, v;\nmov.u32 n, 0;\n"
      "LAB_WAIT:\nld.relaxed.gpu.global.u32 v, [%0];\nsetp.ge.u32 p, v, %1;\n@p bra DONE;\n"
      "add.u32 n, n, 1;\nsetp.lt.u32 q, n, 16777216;\n@q bra LAB_WAIT;\ntrap;\nDONE:\nfence.acquire.gpu;\n}" ::"l"(p),
      "r"(target)
      : "memory");
}
__device__ __forceinline__ void flag_add(unsigned* p) {
  asm volatile("fence.release.gpu;\nred.relaxed.gpu.global.add.u32 [%0], 1;" ::"l"(p) : "memory");
}
__device__ __forceinline__ void flag_add_after_bulk(unsigned* p) {
  asm volatile("fence.proxy.async.global;\nfence.release.gpu;\nred.relaxed.gpu.global.add.u32 [%0], 1;" ::"l"(p) : "memory");
}
__device__ __forceinline__ void flag_add_unf(unsigned* p) {
  asm volatile("fence.proxy.async.global;\nred.relaxed.gpu.global.add.u32 [%0], 1;" ::"l"(p) : "memory");
}
#define FLAG_LN flag_add_after_bulk
#define FLAG_U flag_add_after_bulk
#define FLAG_X flag_add_after_bulk
#define FLAG_KV flag_add_after_bulk
__device__ __forceinline__ unsigned* cnt_ptr(int idx) { return g_cnt + idx * 32; }
__device__ __forceinline__ void fence_proxy_async_global() { asm volatile("fence.proxy.async.global;" ::: "memory"); }
__device__ __forceinline__ void fence_proxy_async_smem() { asm volatile("fence.proxy.async.shared::cta;" ::: "memory"); }
__device__ __forceinline__ void tma2d(uint32_t dst, const CUtensorMap* m, int c0, int c1, uint32_t bar) {
  asm volatile(
      "cp.async.bulk.tensor.2d.shared::cluster.global.mbarrier::complete_tx::bytes [%0], [%1, {%3, %4}], [%2];" ::"r"(dst),
      "l"(m), "r"(bar), "r"(c0), "r"(c1)
      : "memory");
}
__device__ __forceinline__ void tma3d(uint32_t dst, const CUtensorMap* m, int c0, int c1, int c2, uint32_t bar) {
  asm volatile(
      "cp.async.bulk.tensor.3d.shared::cluster.global.mbarrier::complete_tx::bytes [%0], [%1, {%3, %4, %5}], [%2];" ::"r"(dst),
      "l"(m), "r"(bar), "r"(c0), "r"(c1), "r"(c2)
      : "memory");
}
__device__ __forceinline__ void tma4d_store(const CUtensorMap* m, int c0, int c1, int c2, int c3, uint32_t src) {
  asm volatile("cp.async.bulk.tensor.4d.global.shared::cta.bulk_group [%0, {%2, %3, %4, %5}], [%1];" ::"l"(m), "r"(src), "r"(c0), "r"(c1),
               "r"(c2), "r"(c3)
               : "memory");
}
__device__ __forceinline__ void tma2d_prefetch(const CUtensorMap* m, int c0, int c1) {
  asm volatile("cp.async.bulk.prefetch.tensor.2d.L2.global.tile [%0, {%1, %2}];" ::"l"(m), "r"(c0), "r"(c1) : "memory");
}
__device__ __forceinline__ void bulk_load(uint32_t dst, const void* src, uint32_t bytes, uint32_t bar) {
  asm volatile("cp.async.bulk.shared::cluster.global.mbarrier::complete_tx::bytes [%0], [%1], %2, [%3];" ::"r"(dst),
               "l"(src), "r"(bytes), "r"(bar)
               : "memory");
}
__device__ __forceinline__ void bulk_load_mc(uint32_t dst, const void* src, uint32_t bytes, uint32_t bar, uint16_t mask) {
  asm volatile("cp.async.bulk.shared::cluster.global.mbarrier::complete_tx::bytes.multicast::cluster [%0], [%1], %2, [%3], %4;" ::"r"(dst),
               "l"(src), "r"(bytes), "r"(bar), "h"(mask)
               : "memory");
}
__device__ __forceinline__ void mbar_arrive_n(uint32_t bar, uint32_t n) {
  asm volatile("mbarrier.arrive.shared::cta.b64 _, [%0], %1;" ::"r"(bar), "r"(n) : "memory");
}
__device__ __forceinline__ void mbar_arrive_peer(uint32_t remote_bar) {
  asm volatile("mbarrier.arrive.shared::cluster.b64 _, [%0];" ::"r"(remote_bar) : "memory");
}
__device__ __forceinline__ void bulk_store(void* dst, uint32_t src, uint32_t bytes) {
  asm volatile("cp.async.bulk.global.shared::cta.bulk_group [%0], [%1], %2;" ::"l"(dst), "r"(src), "r"(bytes) : "memory");
  asm volatile("cp.async.bulk.commit_group;" ::: "memory");
}
__device__ __forceinline__ void bulk_wait_all() { asm volatile("cp.async.bulk.wait_group 0;" ::: "memory"); }
__device__ __forceinline__ void named_bar(int id, int n) { asm volatile("bar.sync %0, %1;" ::"r"(id), "r"(n) : "memory"); }
__device__ __forceinline__ void named_arrive(int id, int n) { asm volatile("bar.arrive %0, %1;" ::"r"(id), "r"(n) : "memory"); }
__device__ __forceinline__ void bulk_reduce_f32(void* dst, uint32_t src, uint32_t bytes) {
  asm volatile("cp.reduce.async.bulk.global.shared::cta.bulk_group.add.f32 [%0], [%1], %2;" ::"l"(dst), "r"(src), "r"(bytes) : "memory");
  asm volatile("cp.async.bulk.commit_group;" ::: "memory");
}
__device__ __forceinline__ float sqrt_a(float x) { float r; asm("sqrt.approx.ftz.f32 %0, %1;" : "=f"(r) : "f"(x)); return r; }
__device__ __forceinline__ void wg_arrive() { asm volatile("wgmma.fence.sync.aligned;" ::: "memory"); }
__device__ __forceinline__ void wg_commit() { asm volatile("wgmma.commit_group.sync.aligned;" ::: "memory"); }
template <int N>
__device__ __forceinline__ void wg_wait() { asm volatile("wgmma.wait_group.sync.aligned %0;" ::"n"(N) : "memory"); }
__device__ __forceinline__ uint64_t make_desc(uint32_t addr, uint32_t lbo, uint32_t sbo, uint32_t swz) {
  return (uint64_t)((addr & 0x3FFFF) >> 4) | ((uint64_t)(lbo >> 4) << 16) | ((uint64_t)(sbo >> 4) << 32) |
         ((uint64_t)swz << 62);
}
template <int N>
__device__ __forceinline__ void fence_acc(float (&a)[N]) {
#pragma unroll
  for (int i = 0; i < N; i++) asm volatile("" : "+f"(a[i])::"memory");
}
template <int R>
__device__ __forceinline__ void reg_alloc() { asm volatile("setmaxnreg.inc.sync.aligned.u32 %0;" ::"n"(R)); }
template <int R>
__device__ __forceinline__ void reg_dealloc() { asm volatile("setmaxnreg.dec.sync.aligned.u32 %0;" ::"n"(R)); }
__device__ __forceinline__ float bf16r(float x) { return __bfloat162float(__float2bfloat16_rn(x)); }
__device__ __forceinline__ uint32_t pack2(float lo, float hi) {
  uint32_t r;
  asm("cvt.rn.bf16x2.f32 %0, %1, %2;" : "=r"(r) : "f"(hi), "f"(lo));
  return r;
}
__device__ __forceinline__ float lo_f(uint32_t u) { return __uint_as_float(u << 16); }
__device__ __forceinline__ float hi_f(uint32_t u) { return __uint_as_float(u & 0xffff0000u); }
__device__ __forceinline__ float ex2(float x) { float r; asm("ex2.approx.ftz.f32 %0, %1;" : "=f"(r) : "f"(x)); return r; }
__device__ __forceinline__ float rcp(float x) { float r; asm("rcp.approx.ftz.f32 %0, %1;" : "=f"(r) : "f"(x)); return r; }
__device__ __forceinline__ float tanh_f(float x) { float r; asm("tanh.approx.f32 %0, %1;" : "=f"(r) : "f"(x)); return r; }
__device__ __forceinline__ void stmatrix_x4(uint32_t addr, uint32_t r0, uint32_t r1, uint32_t r2, uint32_t r3) {
  asm volatile("stmatrix.sync.aligned.m8n8.x4.shared.b16 [%0], {%1, %2, %3, %4};" ::"r"(addr), "r"(r0), "r"(r1), "r"(r2),
               "r"(r3)
               : "memory");
}
__device__ __forceinline__ void ldmatrix_x4_t(uint32_t addr, uint32_t& r0, uint32_t& r1, uint32_t& r2, uint32_t& r3) {
  asm volatile("ldmatrix.sync.aligned.m8n8.x4.trans.shared.b16 {%0, %1, %2, %3}, [%4];"
               : "=r"(r0), "=r"(r1), "=r"(r2), "=r"(r3)
               : "r"(addr)
               : "memory");
}
__device__ __forceinline__ void ldmatrix_x2_t(uint32_t addr, uint32_t& r0, uint32_t& r1) {
  asm volatile("ldmatrix.sync.aligned.m8n8.x2.trans.shared.b16 {%0, %1}, [%2];" : "=r"(r0), "=r"(r1) : "r"(addr) : "memory");
}
__device__ __forceinline__ void mma16816(float (&c)[4], uint32_t a0, uint32_t a1, uint32_t a2, uint32_t a3, uint32_t b0,
                                         uint32_t b1) {
  asm volatile(
      "mma.sync.aligned.m16n8k16.row.col.f32.bf16.bf16.f32 {%0,%1,%2,%3}, {%4,%5,%6,%7}, {%8,%9}, {%0,%1,%2,%3};"
      : "+f"(c[0]), "+f"(c[1]), "+f"(c[2]), "+f"(c[3])
      : "r"(a0), "r"(a1), "r"(a2), "r"(a3), "r"(b0), "r"(b1));
}
__device__ __forceinline__ void sts128(uint32_t addr, uint32_t a, uint32_t b, uint32_t c, uint32_t d) {
  asm volatile("st.shared.v4.b32 [%0], {%1, %2, %3, %4};" ::"r"(addr), "r"(a), "r"(b), "r"(c), "r"(d) : "memory");
}
__device__ __forceinline__ void sts64(uint32_t addr, uint32_t a, uint32_t b) {
  asm volatile("st.shared.v2.b32 [%0], {%1, %2};" ::"r"(addr), "r"(a), "r"(b) : "memory");
}
#define PROF(role, slot) do { } while (0)
#define CPROF(role, slot) do { } while (0)
#define JPROF(slot) do { } while (0)

template<int N, int TA, int TB> struct WgmmaSS;
template<int N, int TB> struct WgmmaRS;
template<int TA, int TB> struct WgmmaSS<192, TA, TB> {
  static __device__ __forceinline__ void mma(float (&d)[96], uint64_t da, uint64_t db, int scale_d) {
    asm volatile("{\n.reg .pred p;\nsetp.ne.b32 p, %98, 0;\n"
      "wgmma.mma_async.sync.aligned.m64n192k16.f32.bf16.bf16 "
      "{%0, %1, %2, %3, %4, %5, %6, %7, %8, %9, %10, %11, %12, %13, %14, %15, %16, %17, %18, %19, %20, %21, %22, %23, %24, %25, %26, %27, %28, %29, %30, %31, %32, %33, %34, %35, %36, %37, %38, %39, %40, %41, %42, %43, %44, %45, %46, %47, %48, %49, %50, %51, %52, %53, %54, %55, %56, %57, %58, %59, %60, %61, %62, %63, %64, %65, %66, %67, %68, %69, %70, %71, %72, %73, %74, %75, %76, %77, %78, %79, %80, %81, %82, %83, %84, %85, %86, %87, %88, %89, %90, %91, %92, %93, %94, %95}, %96, %97, p, 1, 1, %99, %100;\n}\n"
      : "+f"(d[0]), "+f"(d[1]), "+f"(d[2]), "+f"(d[3]), "+f"(d[4]), "+f"(d[5]), "+f"(d[6]), "+f"(d[7]), "+f"(d[8]), "+f"(d[9]), "+f"(d[10]), "+f"(d[11]), "+f"(d[12]), "+f"(d[13]), "+f"(d[14]), "+f"(d[15]), "+f"(d[16]), "+f"(d[17]), "+f"(d[18]), "+f"(d[19]), "+f"(d[20]), "+f"(d[21]), "+f"(d[22]), "+f"(d[23]), "+f"(d[24]), "+f"(d[25]), "+f"(d[26]), "+f"(d[27]), "+f"(d[28]), "+f"(d[29]), "+f"(d[30]), "+f"(d[31]), "+f"(d[32]), "+f"(d[33]), "+f"(d[34]), "+f"(d[35]), "+f"(d[36]), "+f"(d[37]), "+f"(d[38]), "+f"(d[39]), "+f"(d[40]), "+f"(d[41]), "+f"(d[42]), "+f"(d[43]), "+f"(d[44]), "+f"(d[45]), "+f"(d[46]), "+f"(d[47]), "+f"(d[48]), "+f"(d[49]), "+f"(d[50]), "+f"(d[51]), "+f"(d[52]), "+f"(d[53]), "+f"(d[54]), "+f"(d[55]), "+f"(d[56]), "+f"(d[57]), "+f"(d[58]), "+f"(d[59]), "+f"(d[60]), "+f"(d[61]), "+f"(d[62]), "+f"(d[63]), "+f"(d[64]), "+f"(d[65]), "+f"(d[66]), "+f"(d[67]), "+f"(d[68]), "+f"(d[69]), "+f"(d[70]), "+f"(d[71]), "+f"(d[72]), "+f"(d[73]), "+f"(d[74]), "+f"(d[75]), "+f"(d[76]), "+f"(d[77]), "+f"(d[78]), "+f"(d[79]), "+f"(d[80]), "+f"(d[81]), "+f"(d[82]), "+f"(d[83]), "+f"(d[84]), "+f"(d[85]), "+f"(d[86]), "+f"(d[87]), "+f"(d[88]), "+f"(d[89]), "+f"(d[90]), "+f"(d[91]), "+f"(d[92]), "+f"(d[93]), "+f"(d[94]), "+f"(d[95])
      : "l"(da), "l"(db), "r"(scale_d), "n"(TA), "n"(TB));
  }
};
template<int TA, int TB> struct WgmmaSS<144, TA, TB> {
  static __device__ __forceinline__ void mma(float (&d)[72], uint64_t da, uint64_t db, int scale_d) {
    asm volatile("{\n.reg .pred p;\nsetp.ne.b32 p, %74, 0;\n"
      "wgmma.mma_async.sync.aligned.m64n144k16.f32.bf16.bf16 "
      "{%0, %1, %2, %3, %4, %5, %6, %7, %8, %9, %10, %11, %12, %13, %14, %15, %16, %17, %18, %19, %20, %21, %22, %23, %24, %25, %26, %27, %28, %29, %30, %31, %32, %33, %34, %35, %36, %37, %38, %39, %40, %41, %42, %43, %44, %45, %46, %47, %48, %49, %50, %51, %52, %53, %54, %55, %56, %57, %58, %59, %60, %61, %62, %63, %64, %65, %66, %67, %68, %69, %70, %71}, %72, %73, p, 1, 1, %75, %76;\n}\n"
      : "+f"(d[0]), "+f"(d[1]), "+f"(d[2]), "+f"(d[3]), "+f"(d[4]), "+f"(d[5]), "+f"(d[6]), "+f"(d[7]), "+f"(d[8]), "+f"(d[9]), "+f"(d[10]), "+f"(d[11]), "+f"(d[12]), "+f"(d[13]), "+f"(d[14]), "+f"(d[15]), "+f"(d[16]), "+f"(d[17]), "+f"(d[18]), "+f"(d[19]), "+f"(d[20]), "+f"(d[21]), "+f"(d[22]), "+f"(d[23]), "+f"(d[24]), "+f"(d[25]), "+f"(d[26]), "+f"(d[27]), "+f"(d[28]), "+f"(d[29]), "+f"(d[30]), "+f"(d[31]), "+f"(d[32]), "+f"(d[33]), "+f"(d[34]), "+f"(d[35]), "+f"(d[36]), "+f"(d[37]), "+f"(d[38]), "+f"(d[39]), "+f"(d[40]), "+f"(d[41]), "+f"(d[42]), "+f"(d[43]), "+f"(d[44]), "+f"(d[45]), "+f"(d[46]), "+f"(d[47]), "+f"(d[48]), "+f"(d[49]), "+f"(d[50]), "+f"(d[51]), "+f"(d[52]), "+f"(d[53]), "+f"(d[54]), "+f"(d[55]), "+f"(d[56]), "+f"(d[57]), "+f"(d[58]), "+f"(d[59]), "+f"(d[60]), "+f"(d[61]), "+f"(d[62]), "+f"(d[63]), "+f"(d[64]), "+f"(d[65]), "+f"(d[66]), "+f"(d[67]), "+f"(d[68]), "+f"(d[69]), "+f"(d[70]), "+f"(d[71])
      : "l"(da), "l"(db), "r"(scale_d), "n"(TA), "n"(TB));
  }
};
template<int TA, int TB> struct WgmmaSS<96, TA, TB> {
  static __device__ __forceinline__ void mma(float (&d)[48], uint64_t da, uint64_t db, int scale_d) {
    asm volatile("{\n.reg .pred p;\nsetp.ne.b32 p, %50, 0;\n"
      "wgmma.mma_async.sync.aligned.m64n96k16.f32.bf16.bf16 "
      "{%0, %1, %2, %3, %4, %5, %6, %7, %8, %9, %10, %11, %12, %13, %14, %15, %16, %17, %18, %19, %20, %21, %22, %23, %24, %25, %26, %27, %28, %29, %30, %31, %32, %33, %34, %35, %36, %37, %38, %39, %40, %41, %42, %43, %44, %45, %46, %47}, %48, %49, p, 1, 1, %51, %52;\n}\n"
      : "+f"(d[0]), "+f"(d[1]), "+f"(d[2]), "+f"(d[3]), "+f"(d[4]), "+f"(d[5]), "+f"(d[6]), "+f"(d[7]), "+f"(d[8]), "+f"(d[9]), "+f"(d[10]), "+f"(d[11]), "+f"(d[12]), "+f"(d[13]), "+f"(d[14]), "+f"(d[15]), "+f"(d[16]), "+f"(d[17]), "+f"(d[18]), "+f"(d[19]), "+f"(d[20]), "+f"(d[21]), "+f"(d[22]), "+f"(d[23]), "+f"(d[24]), "+f"(d[25]), "+f"(d[26]), "+f"(d[27]), "+f"(d[28]), "+f"(d[29]), "+f"(d[30]), "+f"(d[31]), "+f"(d[32]), "+f"(d[33]), "+f"(d[34]), "+f"(d[35]), "+f"(d[36]), "+f"(d[37]), "+f"(d[38]), "+f"(d[39]), "+f"(d[40]), "+f"(d[41]), "+f"(d[42]), "+f"(d[43]), "+f"(d[44]), "+f"(d[45]), "+f"(d[46]), "+f"(d[47])
      : "l"(da), "l"(db), "r"(scale_d), "n"(TA), "n"(TB));
  }
};
template<int TA, int TB> struct WgmmaSS<72, TA, TB> {
  static __device__ __forceinline__ void mma(float (&d)[36], uint64_t da, uint64_t db, int scale_d) {
    asm volatile("{\n.reg .pred p;\nsetp.ne.b32 p, %38, 0;\n"
      "wgmma.mma_async.sync.aligned.m64n72k16.f32.bf16.bf16 "
      "{%0, %1, %2, %3, %4, %5, %6, %7, %8, %9, %10, %11, %12, %13, %14, %15, %16, %17, %18, %19, %20, %21, %22, %23, %24, %25, %26, %27, %28, %29, %30, %31, %32, %33, %34, %35}, %36, %37, p, 1, 1, %39, %40;\n}\n"
      : "+f"(d[0]), "+f"(d[1]), "+f"(d[2]), "+f"(d[3]), "+f"(d[4]), "+f"(d[5]), "+f"(d[6]), "+f"(d[7]), "+f"(d[8]), "+f"(d[9]), "+f"(d[10]), "+f"(d[11]), "+f"(d[12]), "+f"(d[13]), "+f"(d[14]), "+f"(d[15]), "+f"(d[16]), "+f"(d[17]), "+f"(d[18]), "+f"(d[19]), "+f"(d[20]), "+f"(d[21]), "+f"(d[22]), "+f"(d[23]), "+f"(d[24]), "+f"(d[25]), "+f"(d[26]), "+f"(d[27]), "+f"(d[28]), "+f"(d[29]), "+f"(d[30]), "+f"(d[31]), "+f"(d[32]), "+f"(d[33]), "+f"(d[34]), "+f"(d[35])
      : "l"(da), "l"(db), "r"(scale_d), "n"(TA), "n"(TB));
  }
};
template<int TA, int TB> struct WgmmaSS<48, TA, TB> {
  static __device__ __forceinline__ void mma(float (&d)[24], uint64_t da, uint64_t db, int scale_d) {
    asm volatile("{\n.reg .pred p;\nsetp.ne.b32 p, %26, 0;\n"
      "wgmma.mma_async.sync.aligned.m64n48k16.f32.bf16.bf16 "
      "{%0, %1, %2, %3, %4, %5, %6, %7, %8, %9, %10, %11, %12, %13, %14, %15, %16, %17, %18, %19, %20, %21, %22, %23}, %24, %25, p, 1, 1, %27, %28;\n}\n"
      : "+f"(d[0]), "+f"(d[1]), "+f"(d[2]), "+f"(d[3]), "+f"(d[4]), "+f"(d[5]), "+f"(d[6]), "+f"(d[7]), "+f"(d[8]), "+f"(d[9]), "+f"(d[10]), "+f"(d[11]), "+f"(d[12]), "+f"(d[13]), "+f"(d[14]), "+f"(d[15]), "+f"(d[16]), "+f"(d[17]), "+f"(d[18]), "+f"(d[19]), "+f"(d[20]), "+f"(d[21]), "+f"(d[22]), "+f"(d[23])
      : "l"(da), "l"(db), "r"(scale_d), "n"(TA), "n"(TB));
  }
};
template<int TA, int TB> struct WgmmaSS<24, TA, TB> {
  static __device__ __forceinline__ void mma(float (&d)[12], uint64_t da, uint64_t db, int scale_d) {
    asm volatile("{\n.reg .pred p;\nsetp.ne.b32 p, %14, 0;\n"
      "wgmma.mma_async.sync.aligned.m64n24k16.f32.bf16.bf16 "
      "{%0, %1, %2, %3, %4, %5, %6, %7, %8, %9, %10, %11}, %12, %13, p, 1, 1, %15, %16;\n}\n"
      : "+f"(d[0]), "+f"(d[1]), "+f"(d[2]), "+f"(d[3]), "+f"(d[4]), "+f"(d[5]), "+f"(d[6]), "+f"(d[7]), "+f"(d[8]), "+f"(d[9]), "+f"(d[10]), "+f"(d[11])
      : "l"(da), "l"(db), "r"(scale_d), "n"(TA), "n"(TB));
  }
};
template<int TB> struct WgmmaRS<80, TB> {
  static __device__ __forceinline__ void mma(float (&d)[40], uint32_t a0, uint32_t a1, uint32_t a2, uint32_t a3, uint64_t db, int scale_d) {
    asm volatile("{\n.reg .pred p;\nsetp.ne.b32 p, %45, 0;\n"
      "wgmma.mma_async.sync.aligned.m64n80k16.f32.bf16.bf16 "
      "{%0, %1, %2, %3, %4, %5, %6, %7, %8, %9, %10, %11, %12, %13, %14, %15, %16, %17, %18, %19, %20, %21, %22, %23, %24, %25, %26, %27, %28, %29, %30, %31, %32, %33, %34, %35, %36, %37, %38, %39}, {%40, %41, %42, %43}, %44, p, 1, 1, %46;\n}\n"
      : "+f"(d[0]), "+f"(d[1]), "+f"(d[2]), "+f"(d[3]), "+f"(d[4]), "+f"(d[5]), "+f"(d[6]), "+f"(d[7]), "+f"(d[8]), "+f"(d[9]), "+f"(d[10]), "+f"(d[11]), "+f"(d[12]), "+f"(d[13]), "+f"(d[14]), "+f"(d[15]), "+f"(d[16]), "+f"(d[17]), "+f"(d[18]), "+f"(d[19]), "+f"(d[20]), "+f"(d[21]), "+f"(d[22]), "+f"(d[23]), "+f"(d[24]), "+f"(d[25]), "+f"(d[26]), "+f"(d[27]), "+f"(d[28]), "+f"(d[29]), "+f"(d[30]), "+f"(d[31]), "+f"(d[32]), "+f"(d[33]), "+f"(d[34]), "+f"(d[35]), "+f"(d[36]), "+f"(d[37]), "+f"(d[38]), "+f"(d[39])
      : "r"(a0), "r"(a1), "r"(a2), "r"(a3), "l"(db), "r"(scale_d), "n"(TB));
  }
};

struct Params {
  const bf16* x; const bf16* wqkv; const bf16* wphi; const bf16* wo; const bf16* b1; const bf16* b2; bf16* out;
};

struct Bars {
  uint64_t full[MST], empty[MST];
  uint64_t ffull[FST], fempty[FST];
  uint64_t stg_done;
  uint64_t xbar[2];
  uint64_t xsent[2];
  uint64_t p0bar;
  uint64_t peer_done;
  uint64_t jfull[2], jack[2];
  uint64_t efull[2];
  uint64_t jend[2];
  int job[2], jring[2];
};
static_assert(sizeof(Bars) <= 1024, "barrier block");

__device__ __forceinline__ uint32_t hsub2u(uint32_t a, uint32_t b) { uint32_t r; asm("sub.rn.bf16x2 %0, %1, %2;" : "=r"(r) : "r"(a), "r"(b)); return r; }
__device__ __forceinline__ void p0_layernorm(uint32_t (&cur)[2][9], int row0, int lane) {
  uint8_t* base = g_xn_img + (size_t)(row0 >> 7) * 9 * 16384 + (row0 & 127) * 128;
  uint32_t ch = lane >> 2, wo = (lane & 3) * 4, stride = 16384;
  float hs = 1.f;
#pragma unroll 1
  for (int pass = 0; pass < 2; pass++) {
    float s1[2], s2[2], sh[2];
#pragma unroll
    for (int r = 0; r < 2; r++) {
      sh[r] = pass == 0 ? __shfl_sync(0xffffffffu, lo_f(cur[r][0]), 0) : 0.f;
      float a0 = 0.f, a1 = 0.f, b0 = 0.f, b1 = 0.f;
#pragma unroll
      for (int c = 0; c < 9; c++) {
        const float d0 = lo_f(cur[r][c]) - sh[r], d1 = hi_f(cur[r][c]) - sh[r];
        a0 += d0; a1 += d1; b0 = fmaf(d0, d0, b0); b1 = fmaf(d1, d1, b1);
      }
      s1[r] = a0 + a1; s2[r] = b0 + b1;
    }
#pragma unroll
    for (int o = 16; o; o >>= 1) {
      s1[0] += __shfl_xor_sync(0xffffffffu, s1[0], o); s2[0] += __shfl_xor_sync(0xffffffffu, s2[0], o);
      s1[1] += __shfl_xor_sync(0xffffffffu, s1[1], o); s2[1] += __shfl_xor_sync(0xffffffffu, s2[1], o);
    }
#pragma unroll
    for (int r = 0; r < 2; r++) {
      const float dm = s1[r] * (1.f / DM);
      const uint32_t mb2 = pack2(sh[r] + dm, sh[r] + dm);
      const float var = bf16r(fmaxf(fmaf(-dm, dm, s2[r] * (1.f / DM)), 0.f));
      const float inv = rcp(bf16r(sqrt_a(bf16r(var + 1e-5f)))) * hs;
      uint8_t* dst = base + r * 128 + ((ch ^ ((row0 + r) & 7)) << 4) + wo;
#pragma unroll
      for (int c = 0; c < 9; c++) {
        const uint32_t d = hsub2u(cur[r][c], mb2);
        cur[r][c] = pack2(lo_f(d) * inv, hi_f(d) * inv);
        *reinterpret_cast<uint32_t*>(dst + c * stride) = cur[r][c];
      }
    }
    base = g_h_img + (size_t)(row0 >> 6) * 3 * 24576 + (row0 & 63) * 128;
    ch = 2 * (lane >> 3) + (lane & 1); wo = ((lane & 7) >> 1) * 4; stride = 8192;
    hs = 0.5f;
    if (threadIdx.x == 0) PROF(1, 9 + pass);
  }
}

__device__ __forceinline__ void p0_fold_a(uint32_t wphi_s  , int part, int lane, uint32_t (&a)[9]) {
  const int g = lane >> 2, j = lane & 3;
#pragma unroll
  for (int i = 0; i < 9; i++) {
    const int fo = (i == 0 || i == 2 || i == 4) ? 0 : (i == 1 || i == 3 || i == 5) ? 8 : 16;
    const int dd = (i == 0 || i == 1 || i == 6) ? 0 : (i == 2 || i == 3 || i == 7) ? 8 : 16;
    const int f = fo + g, d = dd + 2 * j;
    uint32_t v = 0;
    if (f < 18 && d < 18) {
      if (part < 2) {
        unsigned short lo, hi;
        asm volatile("ld.shared.u16 %0, [%1];" : "=h"(lo) : "r"(wphi_s + (d * 18 + f) * 2));
        asm volatile("ld.shared.u16 %0, [%1];" : "=h"(hi) : "r"(wphi_s + ((d + 1) * 18 + f) * 2));
        v = (uint32_t)lo | ((uint32_t)hi << 16);
      } else v = (f == d ? 0x3F80u : 0u) | (f == d + 1 ? 0x3F800000u : 0u);
    }
    a[i] = v;
  }
}
__device__ __forceinline__ void p0_fold(int part, int head, int kq, int warp, int lane, uint32_t tile, const uint32_t (&a)[9]) {
  const int g = lane >> 2, j = lane & 3;
  const uint32_t base = tile + (warp >> 1) * 36 + j * 4;
  uint8_t* img[3];
  int n[3];
  int kbs;
  if (part < 3) {
    int nbase;
    if (part == 0) { img[0] = g_wq_img + (size_t)(head >> 3) * 9 * 18432; nbase = 72 * ((head >> 2) & 1) + 2 * (head & 3); }
    else { img[0] = g_wkv_img + (size_t)(head >> 2) * 9 * 18432; nbase = 72 * (part - 1) + 2 * (head & 3); }
    img[1] = img[0]; img[2] = img[0]; kbs = 18432;
    n[0] = nbase + (g >> 1) * 8 + (g & 1); n[1] = n[0] + 32; n[2] = n[0] + 64;
  } else {
    kbs = 12288;
#pragma unroll
    for (int i = 0; i < 3; i++) {
      const int ch = head * 18 + 8 * i + g, dt = ch / 96, d = ch - 96 * dt;
      img[i] = g_wo_img + (size_t)min(dt, 5) * 9 * 12288;
      n[i] = (d & ~15) + 8 * ((d >> 1) & 1) + 2 * ((d & 15) >> 2) + (d & 1);
    }
  }
#pragma unroll
  for (int i = 0; i < 3; i++) img[i] += n[i] * 128 + (j & 1) * 8;
#pragma unroll 1
  for (int G = (warp & 1) * 5; G < ((warp & 1) ? 9 : 5); G++) {
    uint32_t o[6];
#pragma unroll
    for (int be = 0; be < 2; be++) {
      const int kr = 16 * G + 4 * (g >> 1) + 2 * be + (g & 1);
      int row = kr;
      if (part == 3) {
        row = kr < 128 ? (4 * (kr >> 6) + ((kr & 15) >> 2)) * 18 + 4 * ((kr & 63) >> 4) + (kr & 3)
                       : (4 * ((kr & 3) >> 1) + ((kr - 128) >> 2)) * 18 + 16 + (kr & 1);
      }
      uint32_t b0, b1, b2 = 0;
      asm volatile("ld.shared.b32 %0, [%1];" : "=r"(b0) : "r"(base + row * 144));
      asm volatile("ld.shared.b32 %0, [%1];" : "=r"(b1) : "r"(base + row * 144 + 16));
      if (j == 0) asm volatile("ld.shared.b32 %0, [%1];" : "=r"(b2) : "r"(base + row * 144 + 32));
      float c0[4] = {0.f, 0.f, 0.f, 0.f}, c1[4] = {0.f, 0.f, 0.f, 0.f};
      mma16816(c0, a[0], a[1], a[2], a[3], b0, b1);
      mma16816(c0, a[4], a[5], 0u, 0u, b2, 0u);
      mma16816(c1, a[6], 0u, a[7], 0u, b0, b1);
      mma16816(c1, a[8], 0u, 0u, 0u, b2, 0u);
      o[be] = pack2(c0[0], c0[1]); o[2 + be] = pack2(c0[2], c0[3]); o[4 + be] = pack2(c1[0], c1[1]);
    }
    const int ch = 18 * kq + 2 * G + (j >> 1);
#pragma unroll
    for (int i = 0; i < 3; i++)
      if (i < 2 || g < 2)
        *reinterpret_cast<uint2*>(img[i] + (ch >> 3) * kbs + (((ch & 7) ^ (n[i] & 7)) << 4)) = make_uint2(o[2 * i], o[2 * i + 1]);
  }
}

__device__ __forceinline__ uint32_t hmax2u(uint32_t a, uint32_t b) { uint32_t r; asm("max.bf16x2 %0, %1, %2;" : "=r"(r) : "r"(a), "r"(b)); return r; }
__device__ __forceinline__ uint32_t hmin2u(uint32_t a, uint32_t b) { uint32_t r; asm("min.bf16x2 %0, %1, %2;" : "=r"(r) : "r"(a), "r"(b)); return r; }
__device__ __forceinline__ void dual_softmax18(const uint32_t (&x)[9], uint32_t (&pp)[9], uint32_t (&pn)[9]) {
  constexpr float L2E = 1.4426950408889634f;
  uint32_t mx2 = x[0], mn2 = x[0];
#pragma unroll
  for (int i = 1; i < 9; i++) { mx2 = hmax2u(mx2, x[i]); mn2 = hmin2u(mn2, x[i]); }
  const float cp = -fmaxf(lo_f(mx2), hi_f(mx2)) * L2E, cn = fminf(lo_f(mn2), hi_f(mn2)) * L2E;
  float ep[18], en[18], sp0 = 0.f, sp1 = 0.f, sn0 = 0.f, sn1 = 0.f;
#pragma unroll
  for (int i = 0; i < 9; i++) {
    const float a = lo_f(x[i]), b = hi_f(x[i]);
    ep[2 * i] = ex2(fmaf(a, L2E, cp)); ep[2 * i + 1] = ex2(fmaf(b, L2E, cp));
    en[2 * i] = ex2(fmaf(a, -L2E, cn)); en[2 * i + 1] = ex2(fmaf(b, -L2E, cn));
    sp0 += ep[2 * i]; sp1 += ep[2 * i + 1]; sn0 += en[2 * i]; sn1 += en[2 * i + 1];
  }
  const float ip = rcp(sp0 + sp1), in = rcp(sn0 + sn1);
#pragma unroll
  for (int i = 0; i < 9; i++) {
    pp[i] = pack2(ep[2 * i] * ip, ep[2 * i + 1] * ip);
    pn[i] = pack2(en[2 * i] * in, en[2 * i + 1] * in);
  }
}

template <bool FIRST>
__device__ __forceinline__ void f_kblock(float (&acc0)[72], float (&acc1)[72], uint32_t sA) {
  const uint32_t sB = sA + F_A;
  if (!FIRST) { fence_acc(acc0); fence_acc(acc1); }
  wg_arrive();
#pragma unroll
  for (int k = 0; k < 4; k++) {
    const uint64_t db = make_desc(sB + k * 32, 16, 1024, 1);
    WgmmaSS<144, 0, 0>::mma(acc0, make_desc(sA + k * 32, 16, 1024, 1), db, (FIRST && k == 0) ? 0 : 1);
    WgmmaSS<144, 0, 0>::mma(acc1, make_desc(sA + 8192 + k * 32, 16, 1024, 1), db, (FIRST && k == 0) ? 0 : 1);
  }
  wg_commit();
  fence_acc(acc0); fence_acc(acc1);
}
__device__ __forceinline__ void f_mainloop(float (&acc0)[72], float (&acc1)[72], uint32_t smem, uint32_t full0, uint32_t empty0, int r,
                                           bool leader, int job) {
  int slot = r % FST, prev;
  uint32_t ph = (r / FST) & 1;
  mbar_wait(full0 + 8 * slot, ph);
  JPROF(9);
  f_kblock<true>(acc0, acc1, smem + slot * F_SLOT);
#pragma unroll 1
  for (int kb = 1; kb < 9; kb++) {
    prev = slot;
    if (++slot == FST) { slot = 0; ph ^= 1; }
    mbar_wait(full0 + 8 * slot, ph);
    f_kblock<false>(acc0, acc1, smem + slot * F_SLOT);
    wg_wait<1>();
    if (leader) mbar_arrive(empty0 + 8 * prev);
  }
  wg_wait<0>();
  fence_acc(acc0); fence_acc(acc1);
  if (leader) mbar_arrive(empty0 + 8 * slot);
}

__device__ __forceinline__ void kv_epilogue(uint32_t (&W)[72], uint32_t eb, int wg, int warp, int lane) {
  const int g = lane >> 2, j = lane & 3;
  float d0[24], d1[36], d2[12];
#pragma unroll
  for (int i = 0; i < 24; i++) d0[i] = 0.f;
#pragma unroll
  for (int i = 0; i < 36; i++) d1[i] = 0.f;
#pragma unroll
  for (int i = 0; i < 12; i++) d2[i] = 0.f;
#pragma unroll 1
  for (int mb = 0; mb < 2; mb++) {
    uint32_t pp[2][9], pn[2][9];
#pragma unroll
    for (int rr = 0; rr < 2; rr++) {
      uint32_t x[9];
#pragma unroll
      for (int i = 0; i < 9; i++) x[i] = W[18 * rr + i];
      dual_softmax18(x, pp[rr], pn[rr]);
    }
    if (mb == 1) { wg_wait<0>(); named_bar(1 + wg, 128); }
#pragma unroll
    for (int rr = 0; rr < 2; rr++) {
      const uint32_t t = eb + (2 * warp + rr) * 128 + g * 16;
      const uint32_t a = t + j * 5 * KV_CH, b = t + (20 + 3 * j) * KV_CH;
      sts128(a, pp[rr][0], pp[rr][1], pp[rr][2], pp[rr][3]);
      sts128(a + KV_CH, pp[rr][4], pp[rr][5], pp[rr][6], pp[rr][7]);
      sts128(a + 2 * KV_CH, pp[rr][8], pn[rr][0], pn[rr][1], pn[rr][2]);
      sts128(a + 3 * KV_CH, pn[rr][3], pn[rr][4], pn[rr][5], pn[rr][6]);
      sts64(a + 4 * KV_CH, pn[rr][7], pn[rr][8]);
      sts128(b, W[18 * rr + 9], W[18 * rr + 10], W[18 * rr + 11], W[18 * rr + 12]);
      sts128(b + KV_CH, W[18 * rr + 13], W[18 * rr + 14], W[18 * rr + 15], W[18 * rr + 16]);
      sts128(b + 2 * KV_CH, W[18 * rr + 17], 0x00003F80u, 0u, 0u);
    }
    fence_proxy_async_smem();
    named_bar(1 + wg, 128);
    fence_acc(d0); fence_acc(d1); fence_acc(d2);
    wg_arrive();
#pragma unroll
    for (int ks = 0; ks < 4; ks++) {
      WgmmaSS<48, 1, 1>::mma(d0, make_desc(eb + ks * 256, 128, KV_CH, 0), make_desc(eb + 20 * KV_CH + ks * 256, 128, KV_CH, 0), 1);
      WgmmaSS<72, 1, 1>::mma(d1, make_desc(eb + 8 * KV_CH + ks * 256, 128, KV_CH, 0), make_desc(eb + 23 * KV_CH + ks * 256, 128, KV_CH, 0), 1);
      WgmmaSS<24, 1, 1>::mma(d2, make_desc(eb + 16 * KV_CH + ks * 256, 128, KV_CH, 0), make_desc(eb + 29 * KV_CH + ks * 256, 128, KV_CH, 0), 1);
    }
    wg_commit();
    fence_acc(d0); fence_acc(d1); fence_acc(d2);
#pragma unroll
    for (int i = 0; i < 36; i++) W[i] = W[i + 36];
  }
  wg_wait<0>();
  fence_acc(d0); fence_acc(d1); fence_acc(d2);
  named_bar(1 + wg, 128);
#pragma unroll
  for (int hf = 0; hf < 2; hf++) {
#pragma unroll
    for (int m = 0; m < 3; m++) {
      const int sl = 64 * m + 16 * warp + g + 8 * hf, hs = sl / 40, f = sl - 40 * hs;
      const int hb = m == 0 ? 0 : m == 1 ? 1 : 3, nh = m == 0 ? 2 : m == 1 ? 3 : 1;
      const uint32_t dst = eb + ((hs * 36 + f) * 20 + 2 * j) * 4;
      const bool ok = f < 36 && hs < 4;
#pragma unroll
      for (int nb = 0; nb < 3 * nh; nb++) {
        const float v0 = m == 0 ? d0[(4 * nb + 2 * hf) % 24] : m == 1 ? d1[(4 * nb + 2 * hf) % 36] : d2[(4 * nb + 2 * hf) % 12];
        const float v1 = m == 0 ? d0[(4 * nb + 2 * hf + 1) % 24] : m == 1 ? d1[(4 * nb + 2 * hf + 1) % 36] : d2[(4 * nb + 2 * hf + 1) % 12];
        if (ok && hs == hb + nb / 3 && (nb % 3 < 2 || j < 2))
          asm volatile("st.shared.v2.f32 [%0], {%1, %2};" ::"r"(dst + (nb % 3) * 32), "f"(v0), "f"(v1) : "memory");
      }
    }
  }
  fence_proxy_async_smem();
}

__device__ __forceinline__ void q_epilogue(uint32_t (&W)[72], uint32_t eb, uint8_t* oimg, int gq, int warp, int lane) {
  constexpr float L2E = 1.4426950408889634f;
  uint32_t left0 = 0, left1 = 0;
  const int j = lane & 3;
#pragma unroll 1
  for (int ps = 0; ps < 4; ps++) {
    const int gam = ps & 1;
    const uint32_t kvb = eb + gam * KVB_BYTES;
    uint32_t P[36];
    float cn[2];
    float d[40];
#pragma unroll
    for (int rr = 0; rr < 2; rr++) {
      uint32_t mx2 = W[rr], mn2 = W[rr];
#pragma unroll
      for (int i = 1; i < 9; i++) { mx2 = hmax2u(mx2, W[2 * i + rr]); mn2 = hmin2u(mn2, W[2 * i + rr]); }
      const float cp = -fmaxf(lo_f(mx2), hi_f(mx2)) * L2E;
      cn[rr] = fminf(lo_f(mn2), hi_f(mn2)) * L2E;
      float e[18], s0 = 0.f, s1 = 0.f;
#pragma unroll
      for (int i = 0; i < 9; i++) {
        e[2 * i] = ex2(fmaf(lo_f(W[2 * i + rr]), L2E, cp)); e[2 * i + 1] = ex2(fmaf(hi_f(W[2 * i + rr]), L2E, cp));
        s0 += e[2 * i]; s1 += e[2 * i + 1];
      }
      const float inv = rcp(s0 + s1);
#pragma unroll
      for (int i = 0; i < 9; i++) P[4 * (i >> 1) + 2 * (i & 1) + rr] = pack2(e[2 * i] * inv, e[2 * i + 1] * inv);
    }
    wg_arrive();
#pragma unroll
    for (int t = 0; t < 4; t++)
      WgmmaRS<80, 0>::mma(d, P[4 * t], P[4 * t + 1], P[4 * t + 2], P[4 * t + 3], make_desc(kvb + t * 256, 128, 2304, 0), t > 0);
#pragma unroll
    for (int rr = 0; rr < 2; rr++) {
      float e[18], s0 = 0.f, s1 = 0.f;
#pragma unroll
      for (int i = 0; i < 9; i++) {
        e[2 * i] = ex2(fmaf(lo_f(W[2 * i + rr]), -L2E, cn[rr])); e[2 * i + 1] = ex2(fmaf(hi_f(W[2 * i + rr]), -L2E, cn[rr]));
        s0 += e[2 * i]; s1 += e[2 * i + 1];
      }
      const float inv = rcp(s0 + s1);
#pragma unroll
      for (int i = 0; i < 9; i++) P[4 * ((9 + i) >> 1) + 2 * ((9 + i) & 1) + rr] = pack2(e[2 * i] * inv, e[2 * i + 1] * inv);
    }
    wg_arrive();
#pragma unroll
    for (int t = 4; t < 9; t++)
      WgmmaRS<80, 0>::mma(d, P[4 * t], P[4 * t + 1], P[4 * t + 2], P[4 * t + 3], make_desc(kvb + t * 256, 128, 2304, 0), 1);
    wg_commit();
#pragma unroll
    for (int i = 0; i < 54; i++) W[i] = W[i + 18];
    wg_wait<0>();
    fence_acc(d);
    const int row = warp * 16 + (lane >> 2) + 64 * (ps >> 1);
    uint8_t* base = oimg + row * 128 + (j & 1) * 8;
    const float inv0 = rcp(d[36] + 1e-6f), inv1 = rcp(d[38] + 1e-6f);
#pragma unroll
    for (int sb = 0; sb < 4; sb++) {
      const int ch = gq * 18 + gam * 8 + 2 * sb + (j >> 1);
      uint8_t* dst = base + (ch >> 3) * 16384 + (((ch & 7) ^ (row & 7)) << 4);
      *reinterpret_cast<uint2*>(dst) = make_uint2(pack2(d[8 * sb] * inv0, d[8 * sb + 1] * inv0), pack2(d[8 * sb + 4] * inv0, d[8 * sb + 5] * inv0));
      *reinterpret_cast<uint2*>(dst + 1024) = make_uint2(pack2(d[8 * sb + 2] * inv1, d[8 * sb + 3] * inv1), pack2(d[8 * sb + 6] * inv1, d[8 * sb + 7] * inv1));
    }
    const uint32_t t0 = pack2(d[32] * inv0, d[33] * inv0), t1 = pack2(d[34] * inv1, d[35] * inv1);
    if (gam == 0) { left0 = t0; left1 = t1; }
    else {
      const int ch = gq * 18 + 16 + (j >> 1);
      uint8_t* dst = base + (ch >> 3) * 16384 + (((ch & 7) ^ (row & 7)) << 4);
      *reinterpret_cast<uint2*>(dst) = make_uint2(left0, t0);
      *reinterpret_cast<uint2*>(dst + 1024) = make_uint2(left1, t1);
    }
  }
}

__device__ __forceinline__ void job_decode(int job, int& rb, int& sub) {
  rb = job & 15;
  sub = job < 128 ? job >> 4 : (job - 128) >> 4;
}

__device__ __forceinline__ void f_consumer(Bars* bars, uint32_t smem, int wg, int warp, int lane) {
  const uint32_t full0 = smem_u32(&bars->ffull[0]), empty0 = smem_u32(&bars->fempty[0]);
  const uint32_t eb = smem + EBUF_OFF + wg * EBUF;
  const bool leader = (warp == 0 && lane == 0);
#pragma unroll 1
  for (uint32_t k = 0;; k++) {
    mbar_wait(smem_u32(&bars->jfull[wg]), k & 1);
    const int job = bars->job[wg], r = bars->jring[wg];
    __syncwarp();
    if (leader) mbar_arrive(smem_u32(&bars->jack[wg]));
    if (job < 0) break;
    uint32_t W[72];
    {
      float acc0[72], acc1[72];
      f_mainloop(acc0, acc1, smem, full0, empty0, r, leader, job);
      if (job < 128) {
#pragma unroll
        for (int b = 0; b < 18; b++) {
          W[b] = pack2(acc0[4 * b], acc0[4 * b + 1]); W[18 + b] = pack2(acc0[4 * b + 2], acc0[4 * b + 3]);
          W[36 + b] = pack2(acc1[4 * b], acc1[4 * b + 1]); W[54 + b] = pack2(acc1[4 * b + 2], acc1[4 * b + 3]);
        }
      } else {
#pragma unroll
        for (int i = 0; i < 36; i++) { W[i] = pack2(acc0[2 * i], acc0[2 * i + 1]); W[36 + i] = pack2(acc1[2 * i], acc1[2 * i + 1]); }
      }
    }
    JPROF(1);
    int rb, sub;
    job_decode(job, rb, sub);
    mbar_wait(smem_u32(&bars->efull[wg]), k & 1);
    JPROF(4);
    if (job < 128) kv_epilogue(W, eb, wg, warp, lane);
    else q_epilogue(W, eb, g_o_img + (size_t)rb * 9 * 16384, sub, warp, lane);
    named_bar(1 + wg, 128);
    if (leader) mbar_arrive(smem_u32(&bars->jend[wg]));
    JPROF(2);
  }
}

__device__ __forceinline__ void f_helper(Bars* bars, uint32_t smem, int wg) {
  const uint32_t eb = smem + EBUF_OFF + wg * EBUF, ef = smem_u32(&bars->efull[wg]);
#pragma unroll 1
  for (uint32_t k = 0;; k++) {
    mbar_wait(smem_u32(&bars->jfull[wg]), k & 1);
    const int job = bars->job[wg];
    mbar_arrive(smem_u32(&bars->jack[wg]));
    if (job < 0) break;
    int rb, sub;
    job_decode(job, rb, sub);
    if (job >= 128) {
      flag_wait(cnt_ptr(C_KVB + 2 * sub), 12);
      flag_wait(cnt_ptr(C_KVB + 2 * sub + 1), 12);
      fence_proxy_async_global();
      mbar_expect_tx(ef, EBUF);
      bulk_load(eb, g_kvb_img + 2 * sub * KVB_BYTES, EBUF, ef);
    } else mbar_arrive(ef);
    mbar_wait(smem_u32(&bars->jend[wg]), k & 1);
    if (job < 128) {
      bulk_reduce_f32(g_kvsum + sub * (KVP_BYTES / 4), eb, KVP_BYTES);
      bulk_wait_all();
      FLAG_KV(cnt_ptr(C_KV + sub));
    } else flag_add(cnt_ptr(C_O + rb * 4 + sub));
  }
}

__device__ __forceinline__ void kvb_finalize(int fcta  , int lane) {
  const int piece = fcta % 12;
#pragma unroll 1
  for (int grp = fcta / 12; grp < 8; grp += 2) {
    if (lane == 0) flag_wait(cnt_ptr(C_KV + grp), 16);
    __syncwarp();
    asm volatile("fence.acquire.gpu;" ::: "memory");
    if (lane == 0 && piece == 0) PROF(2, 10 + (grp >> 1));
    uint32_t val[4];
#pragma unroll
    for (int u = 0; u < 4; u++) {
      const int it = min(lane + 32 * u, 119);
      const int c = 15 * piece + (it >> 3), r = it & 7, nb = c / 18, beta = c % 18;
      const int col = nb < 9 ? 2 * nb + (r & 1) : 18;
      const float* sp = g_kvsum + ((grp * 4 + (r >> 1)) * 36 + (beta / 9) * 18 + 2 * (beta % 9)) * 20 + col;
      const float a = __ldcg(sp), b = __ldcg(sp + 20);
      val[u] = (nb < 9 || !(r & 1)) ? pack2(a, b) : 0u;
    }
    uint4* dst = reinterpret_cast<uint4*>(g_kvb_img + grp * KVB_BYTES + piece * 1920);
#pragma unroll
    for (int u = 0; u < 4; u++) {
      const int it = lane + 32 * u, jn = (it & 7) >> 1;
      if (it < 120) dst[it] = make_uint4(jn == 0 ? val[u] : 0u, jn == 1 ? val[u] : 0u, jn == 2 ? val[u] : 0u, jn == 3 ? val[u] : 0u);
    }
    __syncwarp();
    if (lane == 0) { flag_add(cnt_ptr(C_KVB + grp)); if (piece == 0) PROF(2, 14 + (grp >> 1)); }
  }
}

__device__ __forceinline__ void f_producer(Bars* bars, uint32_t smem) {
  const uint32_t full0 = smem_u32(&bars->ffull[0]), empty0 = smem_u32(&bars->fempty[0]);
  const int first = (int)atomicAdd(cnt_ptr(C_JOB), 1u);
  flag_wait(cnt_ptr(C_LN), 128);
  flag_wait(cnt_ptr(C_FOLD), NCTA);
  fence_proxy_async_global();
  int r = 0, nstop = 0;
#pragma unroll 1
  for (uint32_t n = 0; nstop < 2; n++) {
    const int wg = n & 1;
    int job = -1;
    if (nstop == 0) {
      job = n == 0 ? first : (int)atomicAdd(cnt_ptr(C_JOB), 1u);
      if (job >= N_JOBS) job = -1;
    }
    if (n >= 2) mbar_wait(smem_u32(&bars->jack[wg]), ((n >> 1) - 1) & 1);
    bars->job[wg] = job; bars->jring[wg] = r;
    mbar_arrive(smem_u32(&bars->jfull[wg]));
    if (job < 0) { nstop++; continue; }
    int rb, sub;
    job_decode(job, rb, sub);
    const uint8_t* a = g_xn_img + (size_t)rb * 9 * 16384;
    const uint8_t* b = (job < 128 ? g_wkv_img : g_wq_img) + (size_t)sub * 9 * 18432;
#pragma unroll 1
    for (int kb = 0; kb < 9; kb++, r++) {
      const int slot = r % FST;
      mbar_wait(empty0 + 8 * slot, ((r / FST) & 1) ^ 1);
      const uint32_t fb = full0 + 8 * slot, dst = smem + slot * F_SLOT;
      mbar_expect_tx(fb, F_A + F_B);
      bulk_load(dst, a + kb * 16384, F_A, fb);
      bulk_load(dst + F_A, b + kb * 18432, F_B, fb);
    }
  }
}

__device__ __forceinline__ void role_done(int lane) {
  unsigned old = 0;
  if (lane == 0) old = atomicAdd(cnt_ptr(C_DONE), 1u);
  old = __shfl_sync(0xffffffffu, old, 0);
  if (old == N_ROLES - 1) {
#pragma unroll 1
    for (int i = lane; i < C_NUM; i += 32) *reinterpret_cast<volatile unsigned*>(cnt_ptr(i)) = 0u;
  }
}

struct MainPos { int st; uint32_t ph; };
template <bool FIRST>
__device__ __forceinline__ void main_kblock(float (&acc)[96], uint32_t stage, int wg) {
  const uint32_t sA = stage + wg * 8192, sB = stage + M_A;
  if (!FIRST) fence_acc(acc);
  wg_arrive();
#pragma unroll
  for (int k = 0; k < 4; k++)
    WgmmaSS<192, 1, 1>::mma(acc, make_desc(sA + k * 2048, 8192, 1024, 1), make_desc(sB + k * 2048, 8192, 1024, 1), (FIRST && k == 0) ? 0 : 1);
  wg_commit();
  fence_acc(acc);
}
template <int NKB, bool ZERO, class Tail>
__device__ __forceinline__ void main_loop(float (&acc)[96], uint32_t smem, Bars* bars, MainPos& mp, int wg, bool leader,
                                          uint32_t peer_empty0, Tail&& tail) {
  const uint32_t full0 = smem_u32(&bars->full[0]), empty0 = smem_u32(&bars->empty[0]);
  auto release = [&](int st) { mbar_arrive(empty0 + 8 * st); mbar_arrive_peer(peer_empty0 + 8 * st); };
  mbar_wait(full0 + 8 * mp.st, mp.ph);
  if (threadIdx.x == 0) { PROF(2, NKB == 32 ? 20 : 22); CPROF(2, NKB == 32 ? 21 : 23); }
  main_kblock<ZERO>(acc, smem + mp.st * M_STAGE, wg);
  int prev = mp.st;
  if (++mp.st == MST) { mp.st = 0; mp.ph ^= 1; }
#pragma unroll 1
  for (int kb = 1; kb < NKB; kb++) {
    mbar_wait(full0 + 8 * mp.st, mp.ph);
    main_kblock<false>(acc, smem + mp.st * M_STAGE, wg);
    wg_wait<1>();
    if (leader) release(prev);
    prev = mp.st;
    if (++mp.st == MST) { mp.st = 0; mp.ph ^= 1; }
  }
  tail();
  wg_wait<0>();
  fence_acc(acc);
  if (leader) release(prev);
}

__global__ void __cluster_dims__(2, 1, 1) __launch_bounds__(384, 1)
mega_kernel(const __grid_constant__ CUtensorMap tW1, const __grid_constant__ CUtensorMap tW2,
            const __grid_constant__ CUtensorMap tWqkv, const __grid_constant__ CUtensorMap tWo, const Params p) {
  extern __shared__ __align__(1024) uint8_t smem_raw[];
  const uint32_t smem = smem_u32(smem_raw);
  if (smem & 1023) __trap();
  Bars* bars = reinterpret_cast<Bars*>(smem_raw + BARS_OFF);
  const int tid = threadIdx.x, warp = tid >> 5, lane = tid & 31, cta = blockIdx.x;
  const bool is_g1 = cta < N_G1, is_g2 = cta < N_G2;
  const int g1_t = 2 * ((cta >> 1) / 3) + (cta & 1), g1_j = (cta >> 1) % 3;
  const int g1_rot = (5 * (g1_t >> 1)) & 31;
  const int pair = cta >> 1, g2_h = pair & 1, g2_j = (pair >> 1) % 3, g2_i = 2 * (pair / 6) + (cta & 1);

  const int fpart = cta >> 5, fgrp = (cta >> 2) & 7, fkq = cta & 3;
  const uint32_t ftile = smem + FOLD_OFF;

  if (warp >= 8) {
    reg_dealloc<72>();
    if (warp == 8) {
      if (lane == 0) {
        for (int s = 0; s < MST; s++) { mbar_init(smem_u32(&bars->full[s]), 1); mbar_init(smem_u32(&bars->empty[s]), 4); }
        for (int s = 0; s < FST; s++) { mbar_init(smem_u32(&bars->ffull[s]), 1); mbar_init(smem_u32(&bars->fempty[s]), 1); }
        for (int w = 0; w < 2; w++) {
          mbar_init(smem_u32(&bars->xbar[w]), 1);
          mbar_init(smem_u32(&bars->jfull[w]), 1);
          mbar_init(smem_u32(&bars->jack[w]), 2);
          mbar_init(smem_u32(&bars->efull[w]), 1);
          mbar_init(smem_u32(&bars->jend[w]), 1);
        }
        mbar_init(smem_u32(&bars->stg_done), 4);
        mbar_init(smem_u32(&bars->xsent[0]), 1); mbar_init(smem_u32(&bars->xsent[1]), 1);
        mbar_init(smem_u32(&bars->p0bar), 1);
        mbar_init(smem_u32(&bars->peer_done), 2);
        asm volatile("fence.mbarrier_init.release.cluster;" ::: "memory");
        PROF(1, 24);
        if (cta < 128) {
          mbar_expect_tx(smem_u32(&bars->p0bar), FOLD_TILE + FOLD_PHI);
          bulk_load(ftile + FOLD_TILE, p.wphi + fgrp * 4 * 324, FOLD_PHI, smem_u32(&bars->p0bar));
          if (fpart < 3) tma2d(ftile, &tWqkv, fpart * DM + fgrp * 72, fkq * 144, smem_u32(&bars->p0bar));
          else tma2d(ftile, &tWo, fgrp * 72, fkq * 144, smem_u32(&bars->p0bar));
        }
        if (is_g1) {
#pragma unroll 1
          for (int s = 0; s < MST; s++) {
            mbar_expect_tx(smem_u32(&bars->full[s]), M_STAGE);
            tma3d(smem + s * M_STAGE, &tW1, 0, ((s + g1_rot) & 31) * 64, g1_t * 2, smem_u32(&bars->full[s]));
          }
        }
      }
      __syncwarp();
      named_arrive(8, 288);
    }
    asm volatile("barrier.cluster.arrive.relaxed.aligned;" ::: "memory");
    if (warp == 10 && cta < 128) {
      named_bar(3, 288);
      if (lane == 0) {
        flag_add(cnt_ptr(C_LNK + (cta >> 2)));
        asm volatile("red.relaxed.gpu.global.add.u32 [%0], 1;" ::"l"(cnt_ptr(C_LN)) : "memory");
        PROF(1, 11);
      }
      __syncwarp();
    }
    if (warp == 11) { named_bar(4, 288); if (lane == 0) { flag_add(cnt_ptr(C_FOLD)); PROF(1, 13); } }
    __syncwarp();
    asm volatile("barrier.cluster.wait.acquire.aligned;" ::: "memory");
    const uint32_t hoff = (cta & 1) * (M_B / 2);
    const uint8_t* hsrc = g_h_img + (size_t)g1_j * 24576 + hoff;
    if (warp == 8 && lane < MST && is_g1) {
      const int kb = (lane + g1_rot) & 31;
      if (lane == 0) PROF(2, 3);
      flag_wait(cnt_ptr(C_LNK + kb), 4);
      if (lane == 0) PROF(2, 4);
      fence_proxy_async_global();
      if (lane == 0) PROF(2, 0);
      bulk_load_mc(smem + lane * M_STAGE + M_A + hoff, hsrc + (size_t)kb * 3 * 24576, M_B / 2, smem_u32(&bars->full[lane]), 3);
    }
    __syncwarp();
    if (warp == 8 && lane == 0 && is_g1) {
      const uint32_t full0 = smem_u32(&bars->full[0]), empty0 = smem_u32(&bars->empty[0]);
      flag_wait(cnt_ptr(C_LN), 128);
      fence_proxy_async_global();
      int st = 0; uint32_t ph = 0;
#pragma unroll 1
      for (int it = MST; it < 32; it++) {
        const int kb = (it + g1_rot) & 31;
        mbar_wait(empty0 + 8 * st, ph);
        const uint32_t fb = full0 + 8 * st, dst = smem + st * M_STAGE;
        mbar_expect_tx(fb, M_STAGE);
        tma3d(dst, &tW1, 0, kb * 64, g1_t * 2, fb);
        bulk_load_mc(dst + M_A + hoff, hsrc + (size_t)kb * 3 * 24576, M_B / 2, fb, 3);
        if (++st == MST) { st = 0; ph ^= 1; }
      }
      if (is_g2) {
        const uint8_t* usrc = g_u_img + (size_t)g2_j * 72 * 24576 + hoff;
#pragma unroll 1
        for (int m = 0; m < 36; m++) {
          const int kb = 36 * g2_h + (m < 18 ? 2 * m : 2 * (m - 18) + 1);
          mbar_wait(empty0 + 8 * st, ph);
          const uint32_t fb = full0 + 8 * st, dst = smem + st * M_STAGE;
          mbar_expect_tx(fb, M_STAGE);
          tma3d(dst, &tW2, 0, kb * 64, g2_i * 2, fb);
          if (m >= MST) {
            if (m == 18) { flag_wait(cnt_ptr(C_U + (g2_j * 2 + g2_h) * 2 + 1), 18); fence_proxy_async_global(); }
            bulk_load_mc(dst + M_A + hoff, usrc + (size_t)kb * 24576, M_B / 2, fb, 3);
          } else if (m == MST - 1) {
            mbar_wait(smem_u32(&bars->stg_done), 0);
            flag_wait(cnt_ptr(C_U + (g2_j * 2 + g2_h) * 2 + 0), 18);
            fence_proxy_async_global();
            PROF(2, 1);
            int s2 = st + 1;
#pragma unroll 1
            for (int mm = 0; mm < MST; mm++) {
              if (s2 == MST) s2 = 0;
              bulk_load_mc(smem + s2 * M_STAGE + M_A + hoff, usrc + (size_t)(36 * g2_h + 2 * mm) * 24576, M_B / 2, full0 + 8 * s2, 3);
              s2++;
            }
          }
          if (++st == MST) { st = 0; ph ^= 1; }
        }
        const uint8_t* osrc = g_o_img + (size_t)g2_i * 9 * 16384;
        const uint8_t* wsrc = g_wo_img + (size_t)(2 * g2_j + g2_h) * 9 * 12288;
#pragma unroll 1
        for (int m = 0; m < 9; m++) {
          if (m < 8 && !(m & 1)) {
            flag_wait(cnt_ptr(C_O + g2_i * 4 + (m >> 1)), 1);
            fence_proxy_async_global();
            if (m == 6) PROF(2, 2);
          }
          mbar_wait(empty0 + 8 * st, ph);
          const uint32_t fb = full0 + 8 * st, dst = smem + st * M_STAGE;
          mbar_expect_tx(fb, 16384 + 12288);
          bulk_load(dst, osrc + m * 16384, 16384, fb);
          bulk_load(dst + M_A, wsrc + m * 12288, 12288, fb);
          if (++st == MST) { st = 0; ph ^= 1; }
        }
      }
    }
    if (!is_g2) {
      if (lane == 0) {
        if (warp == 8) {
          if (is_g1) { mbar_wait(smem_u32(&bars->stg_done), 0); mbar_wait(smem_u32(&bars->peer_done), 0); }
          f_producer(bars, smem);
        } else if (warp >= 10) f_helper(bars, smem, warp - 10);
      }
      if (warp == 9 && !is_g1) kvb_finalize(cta - N_G1, lane);
    } else if (warp > 8) {
      if (warp < 11 && lane == 0) {
        const int w = warp - 9;
        const uint32_t b0 = smem + (w == 0 ? FOLD_OFF : 3 * M_STAGE + 28672), b1 = smem + (w == 0 ? FOLD_OFF + 12288 : 4 * M_STAGE + 28672);
        mbar_wait(smem_u32(&bars->xsent[w]), 0);
        uint8_t* mine = g_xch + (size_t)(cta * 2 + w) * 24576;
        bulk_store(mine, b0, 12288);
        bulk_store(mine + 12288, b1, 12288);
        bulk_wait_all();
        FLAG_X(cnt_ptr(C_X + cta * 2 + w));
        flag_wait(cnt_ptr(C_X + (cta ^ 2) * 2 + w), 1);
        fence_proxy_async_global();
        const uint8_t* theirs = g_xch + (size_t)((cta ^ 2) * 2 + w) * 24576;
        const uint32_t xb = smem_u32(&bars->xbar[w]);
        mbar_expect_tx(xb, 24576);
        bulk_load(b0, theirs, 12288, xb);
        bulk_load(b1, theirs + 12288, 12288, xb);
      }
    }
    __syncwarp();
    role_done(lane);
  } else {
    if (tid == 0) PROF(0, 0);
    {
      uint32_t raw[2][9];
      if (cta < 128) {
#pragma unroll
        for (int r = 0; r < 2; r++)
#pragma unroll
          for (int c = 0; c < 9; c++)
            raw[r][c] = __ldg(reinterpret_cast<const uint32_t*>(p.x + (size_t)(cta * 16 + warp * 2 + r) * DM + c * 64) + lane);
      }
      asm volatile("barrier.cluster.arrive.relaxed.aligned;" ::: "memory");
      if (cta < 128) {
        p0_layernorm(raw, cta * 16 + warp * 2, lane);
        named_arrive(3, 288);
        if (tid == 0) PROF(0, 1);
        uint32_t fa[9];
        named_bar(8, 288);
        mbar_wait(smem_u32(&bars->p0bar), 0);
        if (tid == 0) PROF(1, 22);
        p0_fold_a(ftile + FOLD_TILE + (warp >> 1) * 648, fpart, lane, fa);
        p0_fold(fpart, 4 * fgrp + (warp >> 1), fkq, warp, lane, ftile, fa);
        if (tid == 0) PROF(1, 12);
      } else {
        uint4* z = reinterpret_cast<uint4*>(g_kvsum);
        for (int i = (cta - 128) * 256 + tid; i < 32 * 36 * 5; i += 1024) z[i] = make_uint4(0u, 0u, 0u, 0u);
        named_bar(8, 288);
      }
      named_arrive(4, 288);
      asm volatile("barrier.cluster.wait.acquire.aligned;" ::: "memory");
    }
    reg_alloc<216>();
    const int wg = warp >> 2, w4 = warp & 3;
    const bool leader = (w4 == 0 && lane == 0);
    const int g = lane >> 2, j = lane & 3;
    if (is_g1) {
      MainPos mp{0, 0};
      float acc[96];
      const uint32_t peer_empty0 = mapa(smem_u32(&bars->empty[0]), (cta & 1) ^ 1);
      {
        const int f0 = g1_t * 128 + wg * 64 + w4 * 16 + g;
        const float hb0 = 0.5f * __bfloat162float(p.b1[f0]), hb1 = 0.5f * __bfloat162float(p.b1[f0 + 8]);
#pragma unroll
        for (int b = 0; b < 24; b++) { acc[4 * b] = hb0; acc[4 * b + 1] = hb0; acc[4 * b + 2] = hb1; acc[4 * b + 3] = hb1; }
      }
      main_loop<32, false>(acc, smem, bars, mp, wg, leader, peer_empty0, []() {});
      if (leader && !is_g2) mbar_arrive_peer(mapa(smem_u32(&bars->peer_done), (cta & 1) ^ 1));
      if (tid == 0) { PROF(0, 2); CPROF(2, 24); }
      {
        named_bar(6, 256);
        if (wg == 1) named_bar(7, 256);
        if (tid == 0) PROF(1, 14);
        const uint32_t stg = smem + (2 + wg) * M_STAGE + M_A;
        const int mi = lane >> 3;
        const int srow = w4 * 16 + (mi & 1) * 8 + (lane & 7);
        const int kb = 2 * g1_t + wg;
        uint8_t* udst = g_u_img + ((size_t)g1_j * 72 + kb) * 24576;
#pragma unroll
        for (int b = 0; b < 24; b += 2) {
          uint32_t r[4];
#pragma unroll
          for (int q = 0; q < 4; q++) {
            const int idx = 4 * (b + (q >> 1)) + 2 * (q & 1);
            float o[2];
#pragma unroll
            for (int e = 0; e < 2; e++) {
              const float w = acc[idx + e];
              const float t = tanh_f(w * fmaf(w * w, 8.f * 0.044715f * 0.7978845608028654f, 2.f * 0.7978845608028654f));
              o[e] = fmaf(w, t, w);
            }
            r[q] = pack2(o[0], o[1]);
          }
          const int blk = b + (mi >> 1);
          stmatrix_x4(stg + (blk >> 3) * 8192 + srow * 128 + (((blk & 7) ^ (srow & 7)) << 4), r[0], r[1], r[2], r[3]);
          if (b == 22 && wg == 0) named_arrive(7, 256);
          if ((b & 7) == 6) {
            fence_proxy_async_smem();
            named_bar(1 + wg, 128);
            if (leader) bulk_store(udst + (b >> 3) * 8192, stg + (b >> 3) * 8192, 8192);
          }
        }
        if (tid == 0) PROF(1, 15);
        if (leader) {
          bulk_wait_all();
          if (tid == 0) PROF(1, 17);
          mbar_arrive(smem_u32(&bars->stg_done));
          mbar_arrive_peer(mapa(smem_u32(&bars->stg_done), (cta & 1) ^ 1));
          FLAG_U(cnt_ptr(C_U + (g1_j * 2 + kb / 36) * 2 + wg));
          if (wg == 0) PROF(0, 3);
        }
        __syncwarp();
      }
      if (is_g2) {
        const int r0 = g2_i * 128 + wg * 64 + w4 * 16 + g;
        const int c0 = g2_j * 192 + g2_h * 96 + 4 * j;
        main_loop<36, true>(acc, smem, bars, mp, wg, leader, peer_empty0, []() {});
        if (tid == 0) { PROF(0, 4); CPROF(2, 25); }
        const int t128 = w4 * 32 + lane;
        const uint32_t inb0 = smem + (wg == 0 ? FOLD_OFF : 3 * M_STAGE + 28672) + t128 * 16;
        const uint32_t inb1 = smem + (wg == 0 ? FOLD_OFF + 12288 : 4 * M_STAGE + 28672) + t128 * 16;
        named_bar(6, 256);
        float yk[48];
#pragma unroll
        for (int bb = 0; bb < 12; bb++) {
          float v0, v1, v2, v3;
          if (g2_h == 0) { v0 = acc[48 + 4 * bb]; v1 = acc[48 + 4 * bb + 1]; v2 = acc[48 + 4 * bb + 2]; v3 = acc[48 + 4 * bb + 3]; }
          else { v0 = acc[4 * bb]; v1 = acc[4 * bb + 1]; v2 = acc[4 * bb + 2]; v3 = acc[4 * bb + 3]; }
          asm volatile("st.shared.v4.f32 [%0], {%1, %2, %3, %4};" ::"r"((bb < 6 ? inb0 : inb1) + (bb % 6) * 2048), "f"(v0), "f"(v1), "f"(v2), "f"(v3) : "memory");
        }
#pragma unroll
        for (int i = 0; i < 48; i++) yk[i] = g2_h == 0 ? acc[i] : acc[48 + i];
        fence_proxy_async_smem();
        named_bar(1 + wg, 128);
        if (leader) mbar_arrive(smem_u32(&bars->xsent[wg]));
        if (tid == 0) PROF(1, 18);
        uint2 xv[6][2];
#pragma unroll
        for (int m = 0; m < 6; m++) {
          xv[m][0] = __ldg(reinterpret_cast<const uint2*>(p.x + (size_t)r0 * DM + c0 + 16 * m));
          xv[m][1] = __ldg(reinterpret_cast<const uint2*>(p.x + (size_t)(r0 + 8) * DM + c0 + 16 * m));
        }
        const float bias2a = __bfloat162float(p.b2[r0]), bias2b = __bfloat162float(p.b2[r0 + 8]);
        float sacc[48];
        {
          const uint32_t full0 = smem_u32(&bars->full[0]), empty0 = smem_u32(&bars->empty[0]);
          int prev = 0;
#pragma unroll 1
          for (int m = 0; m < 9; m++) {
            mbar_wait(full0 + 8 * mp.st, mp.ph);
            const uint32_t sA = smem + mp.st * M_STAGE + wg * 8192, sB = smem + mp.st * M_STAGE + M_A;
            if (m == 0) {
              wg_arrive();
#pragma unroll
              for (int k = 0; k < 4; k++)
                WgmmaSS<96, 0, 0>::mma(sacc, make_desc(sA + k * 32, 16, 1024, 1), make_desc(sB + k * 32, 16, 1024, 1), k > 0);
              wg_commit();
              fence_acc(sacc);
            } else {
              fence_acc(sacc);
              wg_arrive();
#pragma unroll
              for (int k = 0; k < 4; k++)
                WgmmaSS<96, 0, 0>::mma(sacc, make_desc(sA + k * 32, 16, 1024, 1), make_desc(sB + k * 32, 16, 1024, 1), 1);
              wg_commit();
              fence_acc(sacc);
              wg_wait<1>();
              if (leader) mbar_arrive_n(empty0 + 8 * prev, 2);
            }
            prev = mp.st;
            if (++mp.st == MST) { mp.st = 0; mp.ph ^= 1; }
          }
          wg_wait<0>();
          fence_acc(sacc);
        }
        if (tid == 0) PROF(1, 20);
        mbar_wait(smem_u32(&bars->xbar[wg]), 0);
        if (tid == 0) PROF(1, 19);
#pragma unroll
        for (int m = 0; m < 6; m++) {
          uint32_t res[2][2];
#pragma unroll
          for (int h2 = 0; h2 < 2; h2++) {
            const int bb = 2 * m + h2;
            float4 o;
            asm volatile("ld.shared.v4.f32 {%0, %1, %2, %3}, [%4];" : "=f"(o.x), "=f"(o.y), "=f"(o.z), "=f"(o.w) : "r"((bb < 6 ? inb0 : inb1) + (bb % 6) * 2048) : "memory");
            const float y[4] = {yk[4 * bb] + o.x + bias2a, yk[4 * bb + 1] + o.y + bias2a, yk[4 * bb + 2] + o.z + bias2b, yk[4 * bb + 3] + o.w + bias2b};
            const uint32_t x0 = h2 ? xv[m][0].y : xv[m][0].x, x1 = h2 ? xv[m][1].y : xv[m][1].x;
            const float xval[4] = {lo_f(x0), hi_f(x0), lo_f(x1), hi_f(x1)};
            float rr[4];
#pragma unroll
            for (int e = 0; e < 4; e++) {
              const float hy = 0.5f * y[e];
              const float gate = fmaf(hy, tanh_f(hy), hy);
              rr[e] = fmaf(sacc[4 * bb + e], gate, xval[e]);
            }
            res[0][h2] = pack2(rr[0], rr[1]); res[1][h2] = pack2(rr[2], rr[3]);
          }
          *reinterpret_cast<uint2*>(p.out + (size_t)r0 * DM + c0 + 16 * m) = make_uint2(res[0][0], res[0][1]);
          *reinterpret_cast<uint2*>(p.out + (size_t)(r0 + 8) * DM + c0 + 16 * m) = make_uint2(res[1][0], res[1][1]);
        }
        if (tid == 0) PROF(0, 5);
      }
    }
    if (!is_g2) {
      f_consumer(bars, smem, wg, w4, lane);
      if (leader) PROF(wg, 6);
    }
  }
}

typedef CUresult (*EncodeTiledFn)(CUtensorMap*, CUtensorMapDataType, cuuint32_t, void*, const cuuint64_t*, const cuuint64_t*,
                                  const cuuint32_t*, const cuuint32_t*, CUtensorMapInterleave, CUtensorMapSwizzle,
                                  CUtensorMapL2promotion, CUtensorMapFloatOOBfill);

static bool make_map(EncodeTiledFn fn, CUtensorMap* m, const void* ptr, int rank, const cuuint64_t* dims, const cuuint64_t* strides,
                     const cuuint32_t* box, CUtensorMapSwizzle sw) {
  cuuint32_t es[4] = {1, 1, 1, 1};
  return fn(m, CU_TENSOR_MAP_DATA_TYPE_BFLOAT16, rank, const_cast<void*>(ptr), dims, strides, box, es, CU_TENSOR_MAP_INTERLEAVE_NONE, sw,
            CU_TENSOR_MAP_L2_PROMOTION_L2_256B, CU_TENSOR_MAP_FLOAT_OOB_FILL_NONE) == CUDA_SUCCESS;
}

}

extern "C" void kernel_launch(void* const* d_in, const int* in_sizes, int n_in, void* d_out, int out_size) {
  using namespace hk;
  (void)in_sizes; (void)n_in; (void)out_size;
  static EncodeTiledFn fn = nullptr;
  if (!fn) {
    void* f = nullptr;
    cudaDriverEntryPointQueryResult q;
    cudaGetDriverEntryPoint("cuTensorMapEncodeTiled", &f, cudaEnableDefault, &q);
    fn = (EncodeTiledFn)f;
    cudaFuncSetAttribute(mega_kernel, cudaFuncAttributeMaxDynamicSharedMemorySize, SMEM_BYTES);
  }
  CUtensorMap tW1, tW2, tWqkv, tWo;
  {
    const cuuint64_t d1[3] = {64, SEQ, FF / 64}, s1[2] = {FF * 2, 128}, d2[3] = {64, FF, SEQ / 64}, s2[2] = {SEQ * 2, 128};
    const cuuint32_t b3[3] = {64, 64, 2};
    make_map(fn, &tW1, d_in[5], 3, d1, s1, b3, CU_TENSOR_MAP_SWIZZLE_128B);
    make_map(fn, &tW2, d_in[7], 3, d2, s2, b3, CU_TENSOR_MAP_SWIZZLE_128B);
    const cuuint64_t dq[2] = {3 * DM, DM}, sq[1] = {3 * DM * 2}, dw[2] = {DM, DM}, sw[1] = {DM * 2};
    const cuuint32_t b2[2] = {72, 144};
    make_map(fn, &tWqkv, d_in[1], 2, dq, sq, b2, CU_TENSOR_MAP_SWIZZLE_NONE);
    make_map(fn, &tWo, d_in[3], 2, dw, sw, b2, CU_TENSOR_MAP_SWIZZLE_NONE);
  }
  Params p;
  p.x = (const bf16*)d_in[0]; p.wqkv = (const bf16*)d_in[1]; p.wphi = (const bf16*)d_in[2]; p.wo = (const bf16*)d_in[3];
  p.b1 = (const bf16*)d_in[6]; p.b2 = (const bf16*)d_in[8]; p.out = (bf16*)d_out;
  mega_kernel<<<NCTA, 384, SMEM_BYTES>>>(tW1, tW2, tWqkv, tWo, p);
}
```

```cpp
#include <cuda_runtime.h>
#include <cuda_bf16.h>
#include <cuda.h>
#include <stdint.h>

namespace hk {

typedef __nv_bfloat16 bf16;

constexpr int SEQ = 2048, DM = 576, FF = 4608;
constexpr int NCTA = 132;
constexpr int N_G1 = 108;
constexpr int N_G2 = 96;
constexpr int MST = 5;
constexpr int M_A = 16384, M_B = 24576, M_STAGE = M_A + M_B;
#define HK_FST 4
constexpr int FST = HK_FST;
constexpr int F_A = 16384, F_B = 18432, F_SLOT = F_A + F_B;
constexpr int KVB_BYTES = 23040;
constexpr int EBUF = 2 * KVB_BYTES;
constexpr int EBUF_OFF = 4 * F_SLOT;
constexpr int FOLD_OFF = MST * M_STAGE;
constexpr int FOLD_TILE = 144 * 144;
constexpr int FOLD_PHI = 4 * 324 * 2;
constexpr int BARS_OFF = EBUF_OFF + 2 * EBUF;
constexpr int SMEM_BYTES = BARS_OFF + 1024;
constexpr int KV_CH = 1056;
constexpr int N_ROLES = 132 * 4;
constexpr int N_JOBS = 192;
constexpr int KVP_BYTES = 4 * 36 * 20 * 4;
static_assert(FOLD_OFF + FOLD_TILE + FOLD_PHI <= BARS_OFF, "smem layout");

enum { C_LN = 0, C_FOLD = 1, C_JOB = 2, C_DONE = 3, C_U = 4  , C_KV = 16  , C_KVB = 24  ,
       C_O = 32  , C_X = 96  ,
       C_LNK = 288  , C_NUM = 320 };
#define HK_LAYOUT 0
constexpr size_t SZ_XN = 16 * 9 * 16384;
constexpr size_t SZ_H = 32 * 3 * 24576;
constexpr size_t SZ_U = 3 * 72 * 24576;
constexpr size_t SZ_WKV = 8 * 9 * 18432;
constexpr size_t SZ_WQ = 4 * 9 * 18432;
constexpr size_t SZ_WO = 6 * 9 * 12288;
constexpr size_t SZ_O = 16 * 9 * 16384;
constexpr size_t SZ_KVB = 8 * KVB_BYTES;
constexpr size_t SZ_KVS = 32 * 36 * 20 * 4;
constexpr size_t SZ_XCH = 96 * 2 * 24576;
constexpr size_t SZ_CNT = C_NUM * 128;
constexpr size_t O_CNT = 0, O_KVS = O_CNT + SZ_CNT, O_KVB = O_KVS + SZ_KVS, O_WQ = O_KVB + SZ_KVB, O_WKV = O_WQ + SZ_WQ, O_XN = O_WKV + SZ_WKV,
                 O_H = O_XN + SZ_XN, O_WO = O_H + SZ_H, O_O = O_WO + SZ_WO, O_U = O_O + SZ_O, O_XCH = O_U + SZ_U, O_END = O_XCH + SZ_XCH;
__device__ __align__(1024) uint8_t g_scratch[O_END];
#define g_xn_img (g_scratch + O_XN)
#define g_h_img (g_scratch + O_H)
#define g_u_img (g_scratch + O_U)
#define g_wkv_img (g_scratch + O_WKV)
#define g_wq_img (g_scratch + O_WQ)
#define g_wo_img (g_scratch + O_WO)
#define g_o_img (g_scratch + O_O)
#define g_kvb_img (g_scratch + O_KVB)
#define g_xch (g_scratch + O_XCH)
#define g_kvsum (reinterpret_cast<float*>(g_scratch + O_KVS))
#define g_cnt (reinterpret_cast<unsigned*>(g_scratch + O_CNT))

__device__ __forceinline__ uint32_t smem_u32(const void* p) { return (uint32_t)__cvta_generic_to_shared(p); }
__device__ __forceinline__ void mbar_init(uint32_t bar, uint32_t cnt) {
  asm volatile("mbarrier.init.shared::cta.b64 [%0], %1;" ::"r"(bar), "r"(cnt) : "memory");
}
__device__ __forceinline__ void mbar_expect_tx(uint32_t bar, uint32_t bytes) {
  asm volatile("mbarrier.arrive.expect_tx.shared::cta.b64 _, [%0], %1;" ::"r"(bar), "r"(bytes) : "memory");
}
__device__ __forceinline__ void mbar_arrive(uint32_t bar) {
  asm volatile("mbarrier.arrive.shared::cta.b64 _, [%0];" ::"r"(bar) : "memory");
}
__device__ __forceinline__ uint32_t mapa(uint32_t addr, uint32_t cta) {
  uint32_t r;
  asm volatile("mapa.shared::cluster.u32 %0, %1, %2;" : "=r"(r) : "r"(addr), "r"(cta));
  return r;
}
__device__ __forceinline__ void mbar_arrive_remote(uint32_t remote_bar) {
  asm volatile("mbarrier.arrive.release.cluster.shared::cluster.b64 _, [%0];" ::"r"(remote_bar) : "memory");
}
__device__ __forceinline__ void mbar_wait(uint32_t bar, uint32_t parity) {
  asm volatile(
      "{\n.reg .pred p, q;\n.reg .u32 n;\nmov.u32 n, 0;\n"
      "LAB_WAIT:\nmbarrier.try_wait.parity.shared::cta.b64 p, [%0], %1;\n@p bra DONE;\n"
      "add.u32 n, n, 1;\nsetp.lt.u32 q, n, 4194304;\n@q bra LAB_WAIT;\ntrap;\nDONE:\n}" ::"r"(bar),
      "r"(parity)
      : "memory");
}
__device__ __forceinline__ void mbar_wait_cluster(uint32_t bar, uint32_t parity) {
  asm volatile(
      "{\n.reg .pred p, q;\n.reg .u32 n;\nmov.u32 n, 0;\n"
      "LAB_WAIT:\nmbarrier.try_wait.parity.acquire.cluster.shared::cta.b64 p, [%0], %1;\n@p bra DONE;\n"
      "add.u32 n, n, 1;\nsetp.lt.u32 q, n, 4194304;\n@q bra LAB_WAIT;\ntrap;\nDONE:\n}" ::"r"(bar),
      "r"(parity)
      : "memory");
}
__device__ __forceinline__ void flag_wait(const unsigned* p, unsigned target) {
  asm volatile(
      "{\n.reg .pred p, q;\n.reg .u32 n, v;\nmov.u32 n, 0;\n"
      "LAB_WAIT:\nld.relaxed.gpu.global.u32 v, [%0];\nsetp.ge.u32 p, v, %1;\n@p bra DONE;\n"
      "add.u32 n, n, 1;\nsetp.lt.u32 q, n, 16777216;\n@q bra LAB_WAIT;\ntrap;\nDONE:\nfence.acquire.gpu;\n}" ::"l"(p),
      "r"(target)
      : "memory");
}
__device__ __forceinline__ void flag_add(unsigned* p) {
  asm volatile("fence.release.gpu;\nred.relaxed.gpu.global.add.u32 [%0], 1;" ::"l"(p) : "memory");
}
__device__ __forceinline__ void flag_add_after_bulk(unsigned* p) {
  asm volatile("fence.proxy.async.global;\nfence.release.gpu;\nred.relaxed.gpu.global.add.u32 [%0], 1;" ::"l"(p) : "memory");
}
__device__ __forceinline__ void flag_add_unf(unsigned* p) {
  asm volatile("fence.proxy.async.global;\nred.relaxed.gpu.global.add.u32 [%0], 1;" ::"l"(p) : "memory");
}
#define FLAG_LN flag_add_after_bulk
#define FLAG_U flag_add_after_bulk
#define FLAG_X flag_add_after_bulk
#define FLAG_KV flag_add_after_bulk
__device__ __forceinline__ unsigned* cnt_ptr(int idx) { return g_cnt + idx * 32; }
__device__ __forceinline__ void fence_proxy_async_global() { asm volatile("fence.proxy.async.global;" ::: "memory"); }
__device__ __forceinline__ void fence_proxy_async_smem() { asm volatile("fence.proxy.async.shared::cta;" ::: "memory"); }
__device__ __forceinline__ void tma2d(uint32_t dst, const CUtensorMap* m, int c0, int c1, uint32_t bar) {
  asm volatile(
      "cp.async.bulk.tensor.2d.shared::cluster.global.mbarrier::complete_tx::bytes [%0], [%1, {%3, %4}], [%2];" ::"r"(dst),
      "l"(m), "r"(bar), "r"(c0), "r"(c1)
      : "memory");
}
__device__ __forceinline__ void tma3d(uint32_t dst, const CUtensorMap* m, int c0, int c1, int c2, uint32_t bar) {
  asm volatile(
      "cp.async.bulk.tensor.3d.shared::cluster.global.mbarrier::complete_tx::bytes [%0], [%1, {%3, %4, %5}], [%2];" ::"r"(dst),
      "l"(m), "r"(bar), "r"(c0), "r"(c1), "r"(c2)
      : "memory");
}
__device__ __forceinline__ void tma4d_store(const CUtensorMap* m, int c0, int c1, int c2, int c3, uint32_t src) {
  asm volatile("cp.async.bulk.tensor.4d.global.shared::cta.bulk_group [%0, {%2, %3, %4, %5}], [%1];" ::"l"(m), "r"(src), "r"(c0), "r"(c1),
               "r"(c2), "r"(c3)
               : "memory");
}
__device__ __forceinline__ void tma3d_prefetch(const CUtensorMap* m, int c0, int c1, int c2) {
  asm volatile("cp.async.bulk.prefetch.tensor.3d.L2.global.tile [%0, {%1, %2, %3}];" ::"l"(m), "r"(c0), "r"(c1), "r"(c2) : "memory");
}
__device__ __forceinline__ void tma2d_prefetch(const CUtensorMap* m, int c0, int c1) {
  asm volatile("cp.async.bulk.prefetch.tensor.2d.L2.global.tile [%0, {%1, %2}];" ::"l"(m), "r"(c0), "r"(c1) : "memory");
}
__device__ __forceinline__ void bulk_load(uint32_t dst, const void* src, uint32_t bytes, uint32_t bar) {
  asm volatile("cp.async.bulk.shared::cluster.global.mbarrier::complete_tx::bytes [%0], [%1], %2, [%3];" ::"r"(dst),
               "l"(src), "r"(bytes), "r"(bar)
               : "memory");
}
__device__ __forceinline__ void bulk_load_mc(uint32_t dst, const void* src, uint32_t bytes, uint32_t bar, uint16_t mask) {
  asm volatile("cp.async.bulk.shared::cluster.global.mbarrier::complete_tx::bytes.multicast::cluster [%0], [%1], %2, [%3], %4;" ::"r"(dst),
               "l"(src), "r"(bytes), "r"(bar), "h"(mask)
               : "memory");
}
__device__ __forceinline__ void mbar_arrive_n(uint32_t bar, uint32_t n) {
  asm volatile("mbarrier.arrive.shared::cta.b64 _, [%0], %1;" ::"r"(bar), "r"(n) : "memory");
}
__device__ __forceinline__ void mbar_arrive_peer(uint32_t remote_bar) {
  asm volatile("mbarrier.arrive.shared::cluster.b64 _, [%0];" ::"r"(remote_bar) : "memory");
}
__device__ __forceinline__ void bulk_store(void* dst, uint32_t src, uint32_t bytes) {
  asm volatile("cp.async.bulk.global.shared::cta.bulk_group [%0], [%1], %2;" ::"l"(dst), "r"(src), "r"(bytes) : "memory");
  asm volatile("cp.async.bulk.commit_group;" ::: "memory");
}
__device__ __forceinline__ void bulk_wait_all() { asm volatile("cp.async.bulk.wait_group 0;" ::: "memory"); }
__device__ __forceinline__ void named_bar(int id, int n) { asm volatile("bar.sync %0, %1;" ::"r"(id), "r"(n) : "memory"); }
__device__ __forceinline__ void named_arrive(int id, int n) { asm volatile("bar.arrive %0, %1;" ::"r"(id), "r"(n) : "memory"); }
__device__ __forceinline__ void bulk_reduce_f32(void* dst, uint32_t src, uint32_t bytes) {
  asm volatile("cp.reduce.async.bulk.global.shared::cta.bulk_group.add.f32 [%0], [%1], %2;" ::"l"(dst), "r"(src), "r"(bytes) : "memory");
  asm volatile("cp.async.bulk.commit_group;" ::: "memory");
}
__device__ __forceinline__ float sqrt_a(float x) { float r; asm("sqrt.approx.ftz.f32 %0, %1;" : "=f"(r) : "f"(x)); return r; }
__device__ __forceinline__ void wg_arrive() { asm volatile("wgmma.fence.sync.aligned;" ::: "memory"); }
__device__ __forceinline__ void wg_commit() { asm volatile("wgmma.commit_group.sync.aligned;" ::: "memory"); }
template <int N>
__device__ __forceinline__ void wg_wait() { asm volatile("wgmma.wait_group.sync.aligned %0;" ::"n"(N) : "memory"); }
__device__ __forceinline__ uint64_t make_desc(uint32_t addr, uint32_t lbo, uint32_t sbo, uint32_t swz) {
  return (uint64_t)((addr & 0x3FFFF) >> 4) | ((uint64_t)(lbo >> 4) << 16) | ((uint64_t)(sbo >> 4) << 32) |
         ((uint64_t)swz << 62);
}
template <int N>
__device__ __forceinline__ void fence_acc(float (&a)[N]) {
#pragma unroll
  for (int i = 0; i < N; i++) asm volatile("" : "+f"(a[i])::"memory");
}
template <int R>
__device__ __forceinline__ void reg_alloc() { asm volatile("setmaxnreg.inc.sync.aligned.u32 %0;" ::"n"(R)); }
template <int R>
__device__ __forceinline__ void reg_dealloc() { asm volatile("setmaxnreg.dec.sync.aligned.u32 %0;" ::"n"(R)); }
__device__ __forceinline__ float bf16r(float x) { return __bfloat162float(__float2bfloat16_rn(x)); }
__device__ __forceinline__ uint32_t pack2(float lo, float hi) {
  uint32_t r;
  asm("cvt.rn.bf16x2.f32 %0, %1, %2;" : "=r"(r) : "f"(hi), "f"(lo));
  return r;
}
__device__ __forceinline__ float lo_f(uint32_t u) { return __uint_as_float(u << 16); }
__device__ __forceinline__ float hi_f(uint32_t u) { return __uint_as_float(u & 0xffff0000u); }
__device__ __forceinline__ float ex2(float x) { float r; asm("ex2.approx.ftz.f32 %0, %1;" : "=f"(r) : "f"(x)); return r; }
__device__ __forceinline__ float rcp(float x) { float r; asm("rcp.approx.ftz.f32 %0, %1;" : "=f"(r) : "f"(x)); return r; }
__device__ __forceinline__ float tanh_f(float x) { float r; asm("tanh.approx.f32 %0, %1;" : "=f"(r) : "f"(x)); return r; }
__device__ __forceinline__ void stmatrix_x4(uint32_t addr, uint32_t r0, uint32_t r1, uint32_t r2, uint32_t r3) {
  asm volatile("stmatrix.sync.aligned.m8n8.x4.shared.b16 [%0], {%1, %2, %3, %4};" ::"r"(addr), "r"(r0), "r"(r1), "r"(r2),
               "r"(r3)
               : "memory");
}
__device__ __forceinline__ void ldmatrix_x4_t(uint32_t addr, uint32_t& r0, uint32_t& r1, uint32_t& r2, uint32_t& r3) {
  asm volatile("ldmatrix.sync.aligned.m8n8.x4.trans.shared.b16 {%0, %1, %2, %3}, [%4];"
               : "=r"(r0), "=r"(r1), "=r"(r2), "=r"(r3)
               : "r"(addr)
               : "memory");
}
__device__ __forceinline__ void ldmatrix_x2_t(uint32_t addr, uint32_t& r0, uint32_t& r1) {
  asm volatile("ldmatrix.sync.aligned.m8n8.x2.trans.shared.b16 {%0, %1}, [%2];" : "=r"(r0), "=r"(r1) : "r"(addr) : "memory");
}
__device__ __forceinline__ void mma16816(float (&c)[4], uint32_t a0, uint32_t a1, uint32_t a2, uint32_t a3, uint32_t b0,
                                         uint32_t b1) {
  asm volatile(
      "mma.sync.aligned.m16n8k16.row.col.f32.bf16.bf16.f32 {%0,%1,%2,%3}, {%4,%5,%6,%7}, {%8,%9}, {%0,%1,%2,%3};"
      : "+f"(c[0]), "+f"(c[1]), "+f"(c[2]), "+f"(c[3])
      : "r"(a0), "r"(a1), "r"(a2), "r"(a3), "r"(b0), "r"(b1));
}
__device__ __forceinline__ void sts128(uint32_t addr, uint32_t a, uint32_t b, uint32_t c, uint32_t d) {
  asm volatile("st.shared.v4.b32 [%0], {%1, %2, %3, %4};" ::"r"(addr), "r"(a), "r"(b), "r"(c), "r"(d) : "memory");
}
__device__ __forceinline__ void sts64(uint32_t addr, uint32_t a, uint32_t b) {
  asm volatile("st.shared.v2.b32 [%0], {%1, %2};" ::"r"(addr), "r"(a), "r"(b) : "memory");
}
#define PROF(role, slot) do { } while (0)
#define CPROF(role, slot) do { } while (0)
#define JPROF(slot) do { } while (0)

template<int N, int TA, int TB> struct WgmmaSS;
template<int N, int TB> struct WgmmaRS;
template<int TA, int TB> struct WgmmaSS<192, TA, TB> {
  static __device__ __forceinline__ void mma(float (&d)[96], uint64_t da, uint64_t db, int scale_d) {
    asm volatile("{\n.reg .pred p;\nsetp.ne.b32 p, %98, 0;\n"
      "wgmma.mma_async.sync.aligned.m64n192k16.f32.bf16.bf16 "
      "{%0, %1, %2, %3, %4, %5, %6, %7, %8, %9, %10, %11, %12, %13, %14, %15, %16, %17, %18, %19, %20, %21, %22, %23, %24, %25, %26, %27, %28, %29, %30, %31, %32, %33, %34, %35, %36, %37, %38, %39, %40, %41, %42, %43, %44, %45, %46, %47, %48, %49, %50, %51, %52, %53, %54, %55, %56, %57, %58, %59, %60, %61, %62, %63, %64, %65, %66, %67, %68, %69, %70, %71, %72, %73, %74, %75, %76, %77, %78, %79, %80, %81, %82, %83, %84, %85, %86, %87, %88, %89, %90, %91, %92, %93, %94, %95}, %96, %97, p, 1, 1, %99, %100;\n}\n"
      : "+f"(d[0]), "+f"(d[1]), "+f"(d[2]), "+f"(d[3]), "+f"(d[4]), "+f"(d[5]), "+f"(d[6]), "+f"(d[7]), "+f"(d[8]), "+f"(d[9]), "+f"(d[10]), "+f"(d[11]), "+f"(d[12]), "+f"(d[13]), "+f"(d[14]), "+f"(d[15]), "+f"(d[16]), "+f"(d[17]), "+f"(d[18]), "+f"(d[19]), "+f"(d[20]), "+f"(d[21]), "+f"(d[22]), "+f"(d[23]), "+f"(d[24]), "+f"(d[25]), "+f"(d[26]), "+f"(d[27]), "+f"(d[28]), "+f"(d[29]), "+f"(d[30]), "+f"(d[31]), "+f"(d[32]), "+f"(d[33]), "+f"(d[34]), "+f"(d[35]), "+f"(d[36]), "+f"(d[37]), "+f"(d[38]), "+f"(d[39]), "+f"(d[40]), "+f"(d[41]), "+f"(d[42]), "+f"(d[43]), "+f"(d[44]), "+f"(d[45]), "+f"(d[46]), "+f"(d[47]), "+f"(d[48]), "+f"(d[49]), "+f"(d[50]), "+f"(d[51]), "+f"(d[52]), "+f"(d[53]), "+f"(d[54]), "+f"(d[55]), "+f"(d[56]), "+f"(d[57]), "+f"(d[58]), "+f"(d[59]), "+f"(d[60]), "+f"(d[61]), "+f"(d[62]), "+f"(d[63]), "+f"(d[64]), "+f"(d[65]), "+f"(d[66]), "+f"(d[67]), "+f"(d[68]), "+f"(d[69]), "+f"(d[70]), "+f"(d[71]), "+f"(d[72]), "+f"(d[73]), "+f"(d[74]), "+f"(d[75]), "+f"(d[76]), "+f"(d[77]), "+f"(d[78]), "+f"(d[79]), "+f"(d[80]), "+f"(d[81]), "+f"(d[82]), "+f"(d[83]), "+f"(d[84]), "+f"(d[85]), "+f"(d[86]), "+f"(d[87]), "+f"(d[88]), "+f"(d[89]), "+f"(d[90]), "+f"(d[91]), "+f"(d[92]), "+f"(d[93]), "+f"(d[94]), "+f"(d[95])
      : "l"(da), "l"(db), "r"(scale_d), "n"(TA), "n"(TB));
  }
};
template<int TA, int TB> struct WgmmaSS<144, TA, TB> {
  static __device__ __forceinline__ void mma(float (&d)[72], uint64_t da, uint64_t db, int scale_d) {
    asm volatile("{\n.reg .pred p;\nsetp.ne.b32 p, %74, 0;\n"
      "wgmma.mma_async.sync.aligned.m64n144k16.f32.bf16.bf16 "
      "{%0, %1, %2, %3, %4, %5, %6, %7, %8, %9, %10, %11, %12, %13, %14, %15, %16, %17, %18, %19, %20, %21, %22, %23, %24, %25, %26, %27, %28, %29, %30, %31, %32, %33, %34, %35, %36, %37, %38, %39, %40, %41, %42, %43, %44, %45, %46, %47, %48, %49, %50, %51, %52, %53, %54, %55, %56, %57, %58, %59, %60, %61, %62, %63, %64, %65, %66, %67, %68, %69, %70, %71}, %72, %73, p, 1, 1, %75, %76;\n}\n"
      : "+f"(d[0]), "+f"(d[1]), "+f"(d[2]), "+f"(d[3]), "+f"(d[4]), "+f"(d[5]), "+f"(d[6]), "+f"(d[7]), "+f"(d[8]), "+f"(d[9]), "+f"(d[10]), "+f"(d[11]), "+f"(d[12]), "+f"(d[13]), "+f"(d[14]), "+f"(d[15]), "+f"(d[16]), "+f"(d[17]), "+f"(d[18]), "+f"(d[19]), "+f"(d[20]), "+f"(d[21]), "+f"(d[22]), "+f"(d[23]), "+f"(d[24]), "+f"(d[25]), "+f"(d[26]), "+f"(d[27]), "+f"(d[28]), "+f"(d[29]), "+f"(d[30]), "+f"(d[31]), "+f"(d[32]), "+f"(d[33]), "+f"(d[34]), "+f"(d[35]), "+f"(d[36]), "+f"(d[37]), "+f"(d[38]), "+f"(d[39]), "+f"(d[40]), "+f"(d[41]), "+f"(d[42]), "+f"(d[43]), "+f"(d[44]), "+f"(d[45]), "+f"(d[46]), "+f"(d[47]), "+f"(d[48]), "+f"(d[49]), "+f"(d[50]), "+f"(d[51]), "+f"(d[52]), "+f"(d[53]), "+f"(d[54]), "+f"(d[55]), "+f"(d[56]), "+f"(d[57]), "+f"(d[58]), "+f"(d[59]), "+f"(d[60]), "+f"(d[61]), "+f"(d[62]), "+f"(d[63]), "+f"(d[64]), "+f"(d[65]), "+f"(d[66]), "+f"(d[67]), "+f"(d[68]), "+f"(d[69]), "+f"(d[70]), "+f"(d[71])
      : "l"(da), "l"(db), "r"(scale_d), "n"(TA), "n"(TB));
  }
};
template<int TA, int TB> struct WgmmaSS<96, TA, TB> {
  static __device__ __forceinline__ void mma(float (&d)[48], uint64_t da, uint64_t db, int scale_d) {
    asm volatile("{\n.reg .pred p;\nsetp.ne.b32 p, %50, 0;\n"
      "wgmma.mma_async.sync.aligned.m64n96k16.f32.bf16.bf16 "
      "{%0, %1, %2, %3, %4, %5, %6, %7, %8, %9, %10, %11, %12, %13, %14, %15, %16, %17, %18, %19, %20, %21, %22, %23, %24, %25, %26, %27, %28, %29, %30, %31, %32, %33, %34, %35, %36, %37, %38, %39, %40, %41, %42, %43, %44, %45, %46, %47}, %48, %49, p, 1, 1, %51, %52;\n}\n"
      : "+f"(d[0]), "+f"(d[1]), "+f"(d[2]), "+f"(d[3]), "+f"(d[4]), "+f"(d[5]), "+f"(d[6]), "+f"(d[7]), "+f"(d[8]), "+f"(d[9]), "+f"(d[10]), "+f"(d[11]), "+f"(d[12]), "+f"(d[13]), "+f"(d[14]), "+f"(d[15]), "+f"(d[16]), "+f"(d[17]), "+f"(d[18]), "+f"(d[19]), "+f"(d[20]), "+f"(d[21]), "+f"(d[22]), "+f"(d[23]), "+f"(d[24]), "+f"(d[25]), "+f"(d[26]), "+f"(d[27]), "+f"(d[28]), "+f"(d[29]), "+f"(d[30]), "+f"(d[31]), "+f"(d[32]), "+f"(d[33]), "+f"(d[34]), "+f"(d[35]), "+f"(d[36]), "+f"(d[37]), "+f"(d[38]), "+f"(d[39]), "+f"(d[40]), "+f"(d[41]), "+f"(d[42]), "+f"(d[43]), "+f"(d[44]), "+f"(d[45]), "+f"(d[46]), "+f"(d[47])
      : "l"(da), "l"(db), "r"(scale_d), "n"(TA), "n"(TB));
  }
};
template<int TA, int TB> struct WgmmaSS<72, TA, TB> {
  static __device__ __forceinline__ void mma(float (&d)[36], uint64_t da, uint64_t db, int scale_d) {
    asm volatile("{\n.reg .pred p;\nsetp.ne.b32 p, %38, 0;\n"
      "wgmma.mma_async.sync.aligned.m64n72k16.f32.bf16.bf16 "
      "{%0, %1, %2, %3, %4, %5, %6, %7, %8, %9, %10, %11, %12, %13, %14, %15, %16, %17, %18, %19, %20, %21, %22, %23, %24, %25, %26, %27, %28, %29, %30, %31, %32, %33, %34, %35}, %36, %37, p, 1, 1, %39, %40;\n}\n"
      : "+f"(d[0]), "+f"(d[1]), "+f"(d[2]), "+f"(d[3]), "+f"(d[4]), "+f"(d[5]), "+f"(d[6]), "+f"(d[7]), "+f"(d[8]), "+f"(d[9]), "+f"(d[10]), "+f"(d[11]), "+f"(d[12]), "+f"(d[13]), "+f"(d[14]), "+f"(d[15]), "+f"(d[16]), "+f"(d[17]), "+f"(d[18]), "+f"(d[19]), "+f"(d[20]), "+f"(d[21]), "+f"(d[22]), "+f"(d[23]), "+f"(d[24]), "+f"(d[25]), "+f"(d[26]), "+f"(d[27]), "+f"(d[28]), "+f"(d[29]), "+f"(d[30]), "+f"(d[31]), "+f"(d[32]), "+f"(d[33]), "+f"(d[34]), "+f"(d[35])
      : "l"(da), "l"(db), "r"(scale_d), "n"(TA), "n"(TB));
  }
};
template<int TA, int TB> struct WgmmaSS<48, TA, TB> {
  static __device__ __forceinline__ void mma(float (&d)[24], uint64_t da, uint64_t db, int scale_d) {
    asm volatile("{\n.reg .pred p;\nsetp.ne.b32 p, %26, 0;\n"
      "wgmma.mma_async.sync.aligned.m64n48k16.f32.bf16.bf16 "
      "{%0, %1, %2, %3, %4, %5, %6, %7, %8, %9, %10, %11, %12, %13, %14, %15, %16, %17, %18, %19, %20, %21, %22, %23}, %24, %25, p, 1, 1, %27, %28;\n}\n"
      : "+f"(d[0]), "+f"(d[1]), "+f"(d[2]), "+f"(d[3]), "+f"(d[4]), "+f"(d[5]), "+f"(d[6]), "+f"(d[7]), "+f"(d[8]), "+f"(d[9]), "+f"(d[10]), "+f"(d[11]), "+f"(d[12]), "+f"(d[13]), "+f"(d[14]), "+f"(d[15]), "+f"(d[16]), "+f"(d[17]), "+f"(d[18]), "+f"(d[19]), "+f"(d[20]), "+f"(d[21]), "+f"(d[22]), "+f"(d[23])
      : "l"(da), "l"(db), "r"(scale_d), "n"(TA), "n"(TB));
  }
};
template<int TA, int TB> struct WgmmaSS<24, TA, TB> {
  static __device__ __forceinline__ void mma(float (&d)[12], uint64_t da, uint64_t db, int scale_d) {
    asm volatile("{\n.reg .pred p;\nsetp.ne.b32 p, %14, 0;\n"
      "wgmma.mma_async.sync.aligned.m64n24k16.f32.bf16.bf16 "
      "{%0, %1, %2, %3, %4, %5, %6, %7, %8, %9, %10, %11}, %12, %13, p, 1, 1, %15, %16;\n}\n"
      : "+f"(d[0]), "+f"(d[1]), "+f"(d[2]), "+f"(d[3]), "+f"(d[4]), "+f"(d[5]), "+f"(d[6]), "+f"(d[7]), "+f"(d[8]), "+f"(d[9]), "+f"(d[10]), "+f"(d[11])
      : "l"(da), "l"(db), "r"(scale_d), "n"(TA), "n"(TB));
  }
};
template<int TB> struct WgmmaRS<80, TB> {
  static __device__ __forceinline__ void mma(float (&d)[40], uint32_t a0, uint32_t a1, uint32_t a2, uint32_t a3, uint64_t db, int scale_d) {
    asm volatile("{\n.reg .pred p;\nsetp.ne.b32 p, %45, 0;\n"
      "wgmma.mma_async.sync.aligned.m64n80k16.f32.bf16.bf16 "
      "{%0, %1, %2, %3, %4, %5, %6, %7, %8, %9, %10, %11, %12, %13, %14, %15, %16, %17, %18, %19, %20, %21, %22, %23, %24, %25, %26, %27, %28, %29, %30, %31, %32, %33, %34, %35, %36, %37, %38, %39}, {%40, %41, %42, %43}, %44, p, 1, 1, %46;\n}\n"
      : "+f"(d[0]), "+f"(d[1]), "+f"(d[2]), "+f"(d[3]), "+f"(d[4]), "+f"(d[5]), "+f"(d[6]), "+f"(d[7]), "+f"(d[8]), "+f"(d[9]), "+f"(d[10]), "+f"(d[11]), "+f"(d[12]), "+f"(d[13]), "+f"(d[14]), "+f"(d[15]), "+f"(d[16]), "+f"(d[17]), "+f"(d[18]), "+f"(d[19]), "+f"(d[20]), "+f"(d[21]), "+f"(d[22]), "+f"(d[23]), "+f"(d[24]), "+f"(d[25]), "+f"(d[26]), "+f"(d[27]), "+f"(d[28]), "+f"(d[29]), "+f"(d[30]), "+f"(d[31]), "+f"(d[32]), "+f"(d[33]), "+f"(d[34]), "+f"(d[35]), "+f"(d[36]), "+f"(d[37]), "+f"(d[38]), "+f"(d[39])
      : "r"(a0), "r"(a1), "r"(a2), "r"(a3), "l"(db), "r"(scale_d), "n"(TB));
  }
};

struct Params {
  const bf16* x; const bf16* wqkv; const bf16* wphi; const bf16* wo; const bf16* b1; const bf16* b2; bf16* out;
};

struct Bars {
  uint64_t full[MST], empty[MST];
  uint64_t ffull[FST], fempty[FST];
  uint64_t stg_done;
  uint64_t xbar[2];
  uint64_t xsent[2];
  uint64_t p0bar;
  uint64_t lnpub;
  uint64_t peer_done;
  uint64_t jfull[2], jack[2];
  uint64_t efull[2];
  uint64_t jend[2];
  int job[2], jring[2];
};
static_assert(sizeof(Bars) <= 1024, "barrier block");

__device__ __forceinline__ uint32_t hsub2u(uint32_t a, uint32_t b) { uint32_t r; asm("sub.rn.bf16x2 %0, %1, %2;" : "=r"(r) : "r"(a), "r"(b)); return r; }
__device__ __forceinline__ void p0_layernorm(uint32_t (&cur)[2][9], uint32_t stg_xn, uint32_t stg_h, int warp, int lane) {
  const int row0 = warp * 2;
  uint32_t base = stg_xn, ch = lane >> 2, wo = (lane & 3) * 4;
  float hs = 1.f;
#pragma unroll 1
  for (int pass = 0; pass < 2; pass++) {
    float s1[2], s2[2], sh[2];
#pragma unroll
    for (int r = 0; r < 2; r++) {
      sh[r] = pass == 0 ? __shfl_sync(0xffffffffu, lo_f(cur[r][0]), 0) : 0.f;
      float a0 = 0.f, a1 = 0.f, b0 = 0.f, b1 = 0.f;
#pragma unroll
      for (int c = 0; c < 9; c++) {
        const float d0 = lo_f(cur[r][c]) - sh[r], d1 = hi_f(cur[r][c]) - sh[r];
        a0 += d0; a1 += d1; b0 = fmaf(d0, d0, b0); b1 = fmaf(d1, d1, b1);
      }
      s1[r] = a0 + a1; s2[r] = b0 + b1;
    }
#pragma unroll
    for (int o = 16; o; o >>= 1) {
      s1[0] += __shfl_xor_sync(0xffffffffu, s1[0], o); s2[0] += __shfl_xor_sync(0xffffffffu, s2[0], o);
      s1[1] += __shfl_xor_sync(0xffffffffu, s1[1], o); s2[1] += __shfl_xor_sync(0xffffffffu, s2[1], o);
    }
#pragma unroll
    for (int r = 0; r < 2; r++) {
      const float dm = s1[r] * (1.f / DM);
      const uint32_t mb2 = pack2(sh[r] + dm, sh[r] + dm);
      const float var = bf16r(fmaxf(fmaf(-dm, dm, s2[r] * (1.f / DM)), 0.f));
      const float inv = rcp(bf16r(sqrt_a(bf16r(var + 1e-5f)))) * hs;
      const uint32_t dst = base + (row0 + r) * 128 + ((ch ^ ((row0 + r) & 7)) << 4) + wo;
#pragma unroll
      for (int c = 0; c < 9; c++) {
        const uint32_t d = hsub2u(cur[r][c], mb2);
        cur[r][c] = pack2(lo_f(d) * inv, hi_f(d) * inv);
        asm volatile("st.shared.b32 [%0], %1;" ::"r"(dst + c * 2048), "r"(cur[r][c]) : "memory");
      }
    }
    base = stg_h; ch = 2 * (lane >> 3) + (lane & 1); wo = ((lane & 7) >> 1) * 4;
    hs = 0.5f;
    if (threadIdx.x == 0) PROF(1, 9 + pass);
  }
}

__device__ __forceinline__ void p0_fold_a(uint32_t wphi_s  , int part, int lane, uint32_t (&a)[9]) {
  const int g = lane >> 2, j = lane & 3;
#pragma unroll
  for (int i = 0; i < 9; i++) {
    const int fo = (i == 0 || i == 2 || i == 4) ? 0 : (i == 1 || i == 3 || i == 5) ? 8 : 16;
    const int dd = (i == 0 || i == 1 || i == 6) ? 0 : (i == 2 || i == 3 || i == 7) ? 8 : 16;
    const int f = fo + g, d = dd + 2 * j;
    uint32_t v = 0;
    if (f < 18 && d < 18) {
      if (part < 2) {
        unsigned short lo, hi;
        asm volatile("ld.shared.u16 %0, [%1];" : "=h"(lo) : "r"(wphi_s + (d * 18 + f) * 2));
        asm volatile("ld.shared.u16 %0, [%1];" : "=h"(hi) : "r"(wphi_s + ((d + 1) * 18 + f) * 2));
        v = (uint32_t)lo | ((uint32_t)hi << 16);
      } else v = (f == d ? 0x3F80u : 0u) | (f == d + 1 ? 0x3F800000u : 0u);
    }
    a[i] = v;
  }
}
__device__ __forceinline__ void p0_fold(int part, int head, int kq, int warp, int lane, uint32_t tile, const uint32_t (&a)[9]) {
  const int g = lane >> 2, j = lane & 3;
  const uint32_t base = tile + (warp >> 1) * 36 + j * 4;
  uint8_t* img[3];
  int n[3];
  int kbs;
  if (part < 3) {
    int nbase;
    if (part == 0) { img[0] = g_wq_img + (size_t)(head >> 3) * 9 * 18432; nbase = 72 * ((head >> 2) & 1) + 2 * (head & 3); }
    else { img[0] = g_wkv_img + (size_t)(head >> 2) * 9 * 18432; nbase = 72 * (part - 1) + 2 * (head & 3); }
    img[1] = img[0]; img[2] = img[0]; kbs = 18432;
    n[0] = nbase + (g >> 1) * 8 + (g & 1); n[1] = n[0] + 32; n[2] = n[0] + 64;
  } else {
    kbs = 12288;
#pragma unroll
    for (int i = 0; i < 3; i++) {
      const int ch = head * 18 + 8 * i + g, dt = ch / 96, d = ch - 96 * dt;
      img[i] = g_wo_img + (size_t)min(dt, 5) * 9 * 12288;
      n[i] = (d & ~15) + 8 * ((d >> 1) & 1) + 2 * ((d & 15) >> 2) + (d & 1);
    }
  }
#pragma unroll
  for (int i = 0; i < 3; i++) img[i] += n[i] * 128 + (j & 1) * 8;
#pragma unroll 1
  for (int G = (warp & 1) * 5; G < ((warp & 1) ? 9 : 5); G++) {
    uint32_t o[6];
#pragma unroll
    for (int be = 0; be < 2; be++) {
      const int kr = 16 * G + 4 * (g >> 1) + 2 * be + (g & 1);
      int row = kr;
      if (part == 3) {
        row = kr < 128 ? (4 * (kr >> 6) + ((kr & 15) >> 2)) * 18 + 4 * ((kr & 63) >> 4) + (kr & 3)
                       : (4 * ((kr & 3) >> 1) + ((kr - 128) >> 2)) * 18 + 16 + (kr & 1);
      }
      uint32_t b0, b1, b2 = 0;
      asm volatile("ld.shared.b32 %0, [%1];" : "=r"(b0) : "r"(base + row * 144));
      asm volatile("ld.shared.b32 %0, [%1];" : "=r"(b1) : "r"(base + row * 144 + 16));
      if (j == 0) asm volatile("ld.shared.b32 %0, [%1];" : "=r"(b2) : "r"(base + row * 144 + 32));
      float c0[4] = {0.f, 0.f, 0.f, 0.f}, c1[4] = {0.f, 0.f, 0.f, 0.f};
      mma16816(c0, a[0], a[1], a[2], a[3], b0, b1);
      mma16816(c0, a[4], a[5], 0u, 0u, b2, 0u);
      mma16816(c1, a[6], 0u, a[7], 0u, b0, b1);
      mma16816(c1, a[8], 0u, 0u, 0u, b2, 0u);
      o[be] = pack2(c0[0], c0[1]); o[2 + be] = pack2(c0[2], c0[3]); o[4 + be] = pack2(c1[0], c1[1]);
    }
    const int ch = 18 * kq + 2 * G + (j >> 1);
#pragma unroll
    for (int i = 0; i < 3; i++)
      if (i < 2 || g < 2)
        *reinterpret_cast<uint2*>(img[i] + (ch >> 3) * kbs + (((ch & 7) ^ (n[i] & 7)) << 4)) = make_uint2(o[2 * i], o[2 * i + 1]);
  }
}

__device__ __forceinline__ uint32_t hmax2u(uint32_t a, uint32_t b) { uint32_t r; asm("max.bf16x2 %0, %1, %2;" : "=r"(r) : "r"(a), "r"(b)); return r; }
__device__ __forceinline__ uint32_t hmin2u(uint32_t a, uint32_t b) { uint32_t r; asm("min.bf16x2 %0, %1, %2;" : "=r"(r) : "r"(a), "r"(b)); return r; }
__device__ __forceinline__ void dual_softmax18(const uint32_t (&x)[9], uint32_t (&pp)[9], uint32_t (&pn)[9]) {
  constexpr float L2E = 1.4426950408889634f;
  uint32_t mx2 = x[0], mn2 = x[0];
#pragma unroll
  for (int i = 1; i < 9; i++) { mx2 = hmax2u(mx2, x[i]); mn2 = hmin2u(mn2, x[i]); }
  const float cp = -fmaxf(lo_f(mx2), hi_f(mx2)) * L2E, cn = fminf(lo_f(mn2), hi_f(mn2)) * L2E;
  float ep[18], en[18], sp0 = 0.f, sp1 = 0.f, sn0 = 0.f, sn1 = 0.f;
#pragma unroll
  for (int i = 0; i < 9; i++) {
    const float a = lo_f(x[i]), b = hi_f(x[i]);
    ep[2 * i] = ex2(fmaf(a, L2E, cp)); ep[2 * i + 1] = ex2(fmaf(b, L2E, cp));
    en[2 * i] = ex2(fmaf(a, -L2E, cn)); en[2 * i + 1] = ex2(fmaf(b, -L2E, cn));
    sp0 += ep[2 * i]; sp1 += ep[2 * i + 1]; sn0 += en[2 * i]; sn1 += en[2 * i + 1];
  }
  const float ip = rcp(sp0 + sp1), in = rcp(sn0 + sn1);
#pragma unroll
  for (int i = 0; i < 9; i++) {
    pp[i] = pack2(ep[2 * i] * ip, ep[2 * i + 1] * ip);
    pn[i] = pack2(en[2 * i] * in, en[2 * i + 1] * in);
  }
}

template <bool FIRST>
__device__ __forceinline__ void f_kblock(float (&acc0)[72], float (&acc1)[72], uint32_t sA) {
  const uint32_t sB = sA + F_A;
  if (!FIRST) { fence_acc(acc0); fence_acc(acc1); }
  wg_arrive();
#pragma unroll
  for (int k = 0; k < 4; k++) {
    const uint64_t db = make_desc(sB + k * 32, 16, 1024, 1);
    WgmmaSS<144, 0, 0>::mma(acc0, make_desc(sA + k * 32, 16, 1024, 1), db, (FIRST && k == 0) ? 0 : 1);
    WgmmaSS<144, 0, 0>::mma(acc1, make_desc(sA + 8192 + k * 32, 16, 1024, 1), db, (FIRST && k == 0) ? 0 : 1);
  }
  wg_commit();
  fence_acc(acc0); fence_acc(acc1);
}
__device__ __forceinline__ void f_mainloop(float (&acc0)[72], float (&acc1)[72], uint32_t smem, uint32_t full0, uint32_t empty0, int r,
                                           bool leader, int job) {
  int slot = r % FST, prev;
  uint32_t ph = (r / FST) & 1;
  mbar_wait(full0 + 8 * slot, ph);
  JPROF(9);
  f_kblock<true>(acc0, acc1, smem + slot * F_SLOT);
#pragma unroll 1
  for (int kb = 1; kb < 9; kb++) {
    prev = slot;
    if (++slot == FST) { slot = 0; ph ^= 1; }
    mbar_wait(full0 + 8 * slot, ph);
    f_kblock<false>(acc0, acc1, smem + slot * F_SLOT);
    wg_wait<1>();
    if (leader) mbar_arrive(empty0 + 8 * prev);
  }
  wg_wait<0>();
  fence_acc(acc0); fence_acc(acc1);
  if (leader) mbar_arrive(empty0 + 8 * slot);
}

__device__ __forceinline__ void kv_epilogue(uint32_t (&W)[72], uint32_t eb, int wg, int warp, int lane) {
  const int g = lane >> 2, j = lane & 3;
  float d0[24], d1[36], d2[12];
#pragma unroll
  for (int i = 0; i < 24; i++) d0[i] = 0.f;
#pragma unroll
  for (int i = 0; i < 36; i++) d1[i] = 0.f;
#pragma unroll
  for (int i = 0; i < 12; i++) d2[i] = 0.f;
#pragma unroll 1
  for (int mb = 0; mb < 2; mb++) {
    uint32_t pp[2][9], pn[2][9];
#pragma unroll
    for (int rr = 0; rr < 2; rr++) {
      uint32_t x[9];
#pragma unroll
      for (int i = 0; i < 9; i++) x[i] = W[18 * rr + i];
      dual_softmax18(x, pp[rr], pn[rr]);
    }
    if (mb == 1) { wg_wait<0>(); named_bar(1 + wg, 128); }
#pragma unroll
    for (int rr = 0; rr < 2; rr++) {
      const uint32_t t = eb + (2 * warp + rr) * 128 + g * 16;
      const uint32_t a = t + j * 5 * KV_CH, b = t + (20 + 3 * j) * KV_CH;
      sts128(a, pp[rr][0], pp[rr][1], pp[rr][2], pp[rr][3]);
      sts128(a + KV_CH, pp[rr][4], pp[rr][5], pp[rr][6], pp[rr][7]);
      sts128(a + 2 * KV_CH, pp[rr][8], pn[rr][0], pn[rr][1], pn[rr][2]);
      sts128(a + 3 * KV_CH, pn[rr][3], pn[rr][4], pn[rr][5], pn[rr][6]);
      sts64(a + 4 * KV_CH, pn[rr][7], pn[rr][8]);
      sts128(b, W[18 * rr + 9], W[18 * rr + 10], W[18 * rr + 11], W[18 * rr + 12]);
      sts128(b + KV_CH, W[18 * rr + 13], W[18 * rr + 14], W[18 * rr + 15], W[18 * rr + 16]);
      sts128(b + 2 * KV_CH, W[18 * rr + 17], 0x00003F80u, 0u, 0u);
    }
    fence_proxy_async_smem();
    named_bar(1 + wg, 128);
    fence_acc(d0); fence_acc(d1); fence_acc(d2);
    wg_arrive();
#pragma unroll
    for (int ks = 0; ks < 4; ks++) {
      WgmmaSS<48, 1, 1>::mma(d0, make_desc(eb + ks * 256, 128, KV_CH, 0), make_desc(eb + 20 * KV_CH + ks * 256, 128, KV_CH, 0), 1);
      WgmmaSS<72, 1, 1>::mma(d1, make_desc(eb + 8 * KV_CH + ks * 256, 128, KV_CH, 0), make_desc(eb + 23 * KV_CH + ks * 256, 128, KV_CH, 0), 1);
      WgmmaSS<24, 1, 1>::mma(d2, make_desc(eb + 16 * KV_CH + ks * 256, 128, KV_CH, 0), make_desc(eb + 29 * KV_CH + ks * 256, 128, KV_CH, 0), 1);
    }
    wg_commit();
    fence_acc(d0); fence_acc(d1); fence_acc(d2);
#pragma unroll
    for (int i = 0; i < 36; i++) W[i] = W[i + 36];
  }
  wg_wait<0>();
  fence_acc(d0); fence_acc(d1); fence_acc(d2);
  named_bar(1 + wg, 128);
#pragma unroll
  for (int hf = 0; hf < 2; hf++) {
#pragma unroll
    for (int m = 0; m < 3; m++) {
      const int sl = 64 * m + 16 * warp + g + 8 * hf, hs = sl / 40, f = sl - 40 * hs;
      const int hb = m == 0 ? 0 : m == 1 ? 1 : 3, nh = m == 0 ? 2 : m == 1 ? 3 : 1;
      const uint32_t dst = eb + ((hs * 36 + f) * 20 + 2 * j) * 4;
      const bool ok = f < 36 && hs < 4;
#pragma unroll
      for (int nb = 0; nb < 3 * nh; nb++) {
        const float v0 = m == 0 ? d0[(4 * nb + 2 * hf) % 24] : m == 1 ? d1[(4 * nb + 2 * hf) % 36] : d2[(4 * nb + 2 * hf) % 12];
        const float v1 = m == 0 ? d0[(4 * nb + 2 * hf + 1) % 24] : m == 1 ? d1[(4 * nb + 2 * hf + 1) % 36] : d2[(4 * nb + 2 * hf + 1) % 12];
        if (ok && hs == hb + nb / 3 && (nb % 3 < 2 || j < 2))
          asm volatile("st.shared.v2.f32 [%0], {%1, %2};" ::"r"(dst + (nb % 3) * 32), "f"(v0), "f"(v1) : "memory");
      }
    }
  }
  fence_proxy_async_smem();
}

__device__ __forceinline__ void q_epilogue(uint32_t (&W)[72], uint32_t eb, uint8_t* oimg, int gq, int warp, int lane) {
  constexpr float L2E = 1.4426950408889634f;
  uint32_t left0 = 0, left1 = 0;
  const int j = lane & 3;
#pragma unroll 1
  for (int ps = 0; ps < 4; ps++) {
    const int gam = ps & 1;
    const uint32_t kvb = eb + gam * KVB_BYTES;
    uint32_t P[36];
    float cn[2];
    float d[40];
#pragma unroll
    for (int rr = 0; rr < 2; rr++) {
      uint32_t mx2 = W[rr], mn2 = W[rr];
#pragma unroll
      for (int i = 1; i < 9; i++) { mx2 = hmax2u(mx2, W[2 * i + rr]); mn2 = hmin2u(mn2, W[2 * i + rr]); }
      const float cp = -fmaxf(lo_f(mx2), hi_f(mx2)) * L2E;
      cn[rr] = fminf(lo_f(mn2), hi_f(mn2)) * L2E;
      float e[18], s0 = 0.f, s1 = 0.f;
#pragma unroll
      for (int i = 0; i < 9; i++) {
        e[2 * i] = ex2(fmaf(lo_f(W[2 * i + rr]), L2E, cp)); e[2 * i + 1] = ex2(fmaf(hi_f(W[2 * i + rr]), L2E, cp));
        s0 += e[2 * i]; s1 += e[2 * i + 1];
      }
      const float inv = rcp(s0 + s1);
#pragma unroll
      for (int i = 0; i < 9; i++) P[4 * (i >> 1) + 2 * (i & 1) + rr] = pack2(e[2 * i] * inv, e[2 * i + 1] * inv);
    }
    wg_arrive();
#pragma unroll
    for (int t = 0; t < 4; t++)
      WgmmaRS<80, 0>::mma(d, P[4 * t], P[4 * t + 1], P[4 * t + 2], P[4 * t + 3], make_desc(kvb + t * 256, 128, 2304, 0), t > 0);
#pragma unroll
    for (int rr = 0; rr < 2; rr++) {
      float e[18], s0 = 0.f, s1 = 0.f;
#pragma unroll
      for (int i = 0; i < 9; i++) {
        e[2 * i] = ex2(fmaf(lo_f(W[2 * i + rr]), -L2E, cn[rr])); e[2 * i + 1] = ex2(fmaf(hi_f(W[2 * i + rr]), -L2E, cn[rr]));
        s0 += e[2 * i]; s1 += e[2 * i + 1];
      }
      const float inv = rcp(s0 + s1);
#pragma unroll
      for (int i = 0; i < 9; i++) P[4 * ((9 + i) >> 1) + 2 * ((9 + i) & 1) + rr] = pack2(e[2 * i] * inv, e[2 * i + 1] * inv);
    }
    wg_arrive();
#pragma unroll
    for (int t = 4; t < 9; t++)
      WgmmaRS<80, 0>::mma(d, P[4 * t], P[4 * t + 1], P[4 * t + 2], P[4 * t + 3], make_desc(kvb + t * 256, 128, 2304, 0), 1);
    wg_commit();
#pragma unroll
    for (int i = 0; i < 54; i++) W[i] = W[i + 18];
    wg_wait<0>();
    fence_acc(d);
    const int row = warp * 16 + (lane >> 2) + 64 * (ps >> 1);
    uint8_t* base = oimg + row * 128 + (j & 1) * 8;
    const float inv0 = rcp(d[36] + 1e-6f), inv1 = rcp(d[38] + 1e-6f);
#pragma unroll
    for (int sb = 0; sb < 4; sb++) {
      const int ch = gq * 18 + gam * 8 + 2 * sb + (j >> 1);
      uint8_t* dst = base + (ch >> 3) * 16384 + (((ch & 7) ^ (row & 7)) << 4);
      *reinterpret_cast<uint2*>(dst) = make_uint2(pack2(d[8 * sb] * inv0, d[8 * sb + 1] * inv0), pack2(d[8 * sb + 4] * inv0, d[8 * sb + 5] * inv0));
      *reinterpret_cast<uint2*>(dst + 1024) = make_uint2(pack2(d[8 * sb + 2] * inv1, d[8 * sb + 3] * inv1), pack2(d[8 * sb + 6] * inv1, d[8 * sb + 7] * inv1));
    }
    const uint32_t t0 = pack2(d[32] * inv0, d[33] * inv0), t1 = pack2(d[34] * inv1, d[35] * inv1);
    if (gam == 0) { left0 = t0; left1 = t1; }
    else {
      const int ch = gq * 18 + 16 + (j >> 1);
      uint8_t* dst = base + (ch >> 3) * 16384 + (((ch & 7) ^ (row & 7)) << 4);
      *reinterpret_cast<uint2*>(dst) = make_uint2(left0, t0);
      *reinterpret_cast<uint2*>(dst + 1024) = make_uint2(left1, t1);
    }
  }
}

__device__ __forceinline__ void job_decode(int job, int& rb, int& sub) {
  rb = job & 15;
  sub = job < 128 ? job >> 4 : (job - 128) >> 4;
}

__device__ __forceinline__ void f_consumer(Bars* bars, uint32_t smem, int wg, int warp, int lane) {
  const uint32_t full0 = smem_u32(&bars->ffull[0]), empty0 = smem_u32(&bars->fempty[0]);
  const uint32_t eb = smem + EBUF_OFF + wg * EBUF;
  const bool leader = (warp == 0 && lane == 0);
#pragma unroll 1
  for (uint32_t k = 0;; k++) {
    mbar_wait(smem_u32(&bars->jfull[wg]), k & 1);
    const int job = bars->job[wg], r = bars->jring[wg];
    __syncwarp();
    if (leader) mbar_arrive(smem_u32(&bars->jack[wg]));
    if (job < 0) break;
    uint32_t W[72];
    {
      float acc0[72], acc1[72];
      f_mainloop(acc0, acc1, smem, full0, empty0, r, leader, job);
      if (job < 128) {
#pragma unroll
        for (int b = 0; b < 18; b++) {
          W[b] = pack2(acc0[4 * b], acc0[4 * b + 1]); W[18 + b] = pack2(acc0[4 * b + 2], acc0[4 * b + 3]);
          W[36 + b] = pack2(acc1[4 * b], acc1[4 * b + 1]); W[54 + b] = pack2(acc1[4 * b + 2], acc1[4 * b + 3]);
        }
      } else {
#pragma unroll
        for (int i = 0; i < 36; i++) { W[i] = pack2(acc0[2 * i], acc0[2 * i + 1]); W[36 + i] = pack2(acc1[2 * i], acc1[2 * i + 1]); }
      }
    }
    JPROF(1);
    int rb, sub;
    job_decode(job, rb, sub);
    mbar_wait(smem_u32(&bars->efull[wg]), k & 1);
    JPROF(4);
    if (job < 128) kv_epilogue(W, eb, wg, warp, lane);
    else q_epilogue(W, eb, g_o_img + (size_t)rb * 9 * 16384, sub, warp, lane);
    named_bar(1 + wg, 128);
    if (leader) mbar_arrive(smem_u32(&bars->jend[wg]));
    JPROF(2);
  }
}

__device__ __forceinline__ void f_helper(Bars* bars, uint32_t smem, int wg) {
  const uint32_t eb = smem + EBUF_OFF + wg * EBUF, ef = smem_u32(&bars->efull[wg]);
#pragma unroll 1
  for (uint32_t k = 0;; k++) {
    mbar_wait(smem_u32(&bars->jfull[wg]), k & 1);
    const int job = bars->job[wg];
    mbar_arrive(smem_u32(&bars->jack[wg]));
    if (job < 0) break;
    int rb, sub;
    job_decode(job, rb, sub);
    if (job >= 128) {
      flag_wait(cnt_ptr(C_KVB + 2 * sub), 12);
      flag_wait(cnt_ptr(C_KVB + 2 * sub + 1), 12);
      fence_proxy_async_global();
      mbar_expect_tx(ef, EBUF);
      bulk_load(eb, g_kvb_img + 2 * sub * KVB_BYTES, EBUF, ef);
    } else mbar_arrive(ef);
    mbar_wait(smem_u32(&bars->jend[wg]), k & 1);
    if (job < 128) {
      bulk_reduce_f32(g_kvsum + sub * (KVP_BYTES / 4), eb, KVP_BYTES);
      bulk_wait_all();
      FLAG_KV(cnt_ptr(C_KV + sub));
    } else flag_add(cnt_ptr(C_O + rb * 4 + sub));
  }
}

__device__ __forceinline__ void kvb_finalize(int fcta  , int lane) {
  const int piece = fcta % 12;
#pragma unroll 1
  for (int grp = fcta / 12; grp < 8; grp += 2) {
    if (lane == 0) flag_wait(cnt_ptr(C_KV + grp), 16);
    __syncwarp();
    asm volatile("fence.acquire.gpu;" ::: "memory");
    if (lane == 0 && piece == 0) PROF(2, 10 + (grp >> 1));
    uint32_t val[4];
#pragma unroll
    for (int u = 0; u < 4; u++) {
      const int it = min(lane + 32 * u, 119);
      const int c = 15 * piece + (it >> 3), r = it & 7, nb = c / 18, beta = c % 18;
      const int col = nb < 9 ? 2 * nb + (r & 1) : 18;
      const float* sp = g_kvsum + ((grp * 4 + (r >> 1)) * 36 + (beta / 9) * 18 + 2 * (beta % 9)) * 20 + col;
      const float a = __ldcg(sp), b = __ldcg(sp + 20);
      val[u] = (nb < 9 || !(r & 1)) ? pack2(a, b) : 0u;
    }
    uint4* dst = reinterpret_cast<uint4*>(g_kvb_img + grp * KVB_BYTES + piece * 1920);
#pragma unroll
    for (int u = 0; u < 4; u++) {
      const int it = lane + 32 * u, jn = (it & 7) >> 1;
      if (it < 120) dst[it] = make_uint4(jn == 0 ? val[u] : 0u, jn == 1 ? val[u] : 0u, jn == 2 ? val[u] : 0u, jn == 3 ? val[u] : 0u);
    }
    __syncwarp();
    if (lane == 0) { flag_add(cnt_ptr(C_KVB + grp)); if (piece == 0) PROF(2, 14 + (grp >> 1)); }
  }
}

__device__ __forceinline__ void f_producer(Bars* bars, uint32_t smem) {
  const uint32_t full0 = smem_u32(&bars->ffull[0]), empty0 = smem_u32(&bars->fempty[0]);
  const int first = (int)atomicAdd(cnt_ptr(C_JOB), 1u);
  flag_wait(cnt_ptr(C_LN), 128);
  flag_wait(cnt_ptr(C_FOLD), NCTA);
  fence_proxy_async_global();
  int r = 0, nstop = 0;
#pragma unroll 1
  for (uint32_t n = 0; nstop < 2; n++) {
    const int wg = n & 1;
    int job = -1;
    if (nstop == 0) {
      job = n == 0 ? first : (int)atomicAdd(cnt_ptr(C_JOB), 1u);
      if (job >= N_JOBS) job = -1;
    }
    if (n >= 2) mbar_wait(smem_u32(&bars->jack[wg]), ((n >> 1) - 1) & 1);
    bars->job[wg] = job; bars->jring[wg] = r;
    mbar_arrive(smem_u32(&bars->jfull[wg]));
    if (job < 0) { nstop++; continue; }
    int rb, sub;
    job_decode(job, rb, sub);
    const uint8_t* a = g_xn_img + (size_t)rb * 9 * 16384;
    const uint8_t* b = (job < 128 ? g_wkv_img : g_wq_img) + (size_t)sub * 9 * 18432;
#pragma unroll 1
    for (int kb = 0; kb < 9; kb++, r++) {
      const int slot = r % FST;
      mbar_wait(empty0 + 8 * slot, ((r / FST) & 1) ^ 1);
      const uint32_t fb = full0 + 8 * slot, dst = smem + slot * F_SLOT;
      mbar_expect_tx(fb, F_A + F_B);
      bulk_load(dst, a + kb * 16384, F_A, fb);
      bulk_load(dst + F_A, b + kb * 18432, F_B, fb);
    }
  }
}

__device__ __forceinline__ void role_done(int lane) {
  unsigned old = 0;
  if (lane == 0) old = atomicAdd(cnt_ptr(C_DONE), 1u);
  old = __shfl_sync(0xffffffffu, old, 0);
  if (old == N_ROLES - 1) {
#pragma unroll 1
    for (int i = lane; i < C_NUM; i += 32) *reinterpret_cast<volatile unsigned*>(cnt_ptr(i)) = 0u;
  }
}

struct MainPos { int st; uint32_t ph; };
template <bool FIRST>
__device__ __forceinline__ void main_kblock(float (&acc)[96], uint32_t stage, int wg) {
  const uint32_t sA = stage + wg * 8192, sB = stage + M_A;
  if (!FIRST) fence_acc(acc);
  wg_arrive();
#pragma unroll
  for (int k = 0; k < 4; k++)
    WgmmaSS<192, 1, 1>::mma(acc, make_desc(sA + k * 2048, 8192, 1024, 1), make_desc(sB + k * 2048, 8192, 1024, 1), (FIRST && k == 0) ? 0 : 1);
  wg_commit();
  fence_acc(acc);
}
template <int NKB, bool ZERO, class Tail>
__device__ __forceinline__ void main_loop(float (&acc)[96], uint32_t smem, Bars* bars, MainPos& mp, int wg, bool leader,
                                          uint32_t peer_empty0, Tail&& tail) {
  const uint32_t full0 = smem_u32(&bars->full[0]), empty0 = smem_u32(&bars->empty[0]);
  auto release = [&](int st) { mbar_arrive(empty0 + 8 * st); mbar_arrive_peer(peer_empty0 + 8 * st); };
  mbar_wait(full0 + 8 * mp.st, mp.ph);
  if (threadIdx.x == 0) { PROF(2, NKB == 32 ? 20 : 22); CPROF(2, NKB == 32 ? 21 : 23); }
  main_kblock<ZERO>(acc, smem + mp.st * M_STAGE, wg);
  int prev = mp.st;
  if (++mp.st == MST) { mp.st = 0; mp.ph ^= 1; }
#pragma unroll 1
  for (int kb = 1; kb < NKB; kb++) {
    mbar_wait(full0 + 8 * mp.st, mp.ph);
    main_kblock<false>(acc, smem + mp.st * M_STAGE, wg);
    wg_wait<1>();
    if (leader) release(prev);
    prev = mp.st;
    if (++mp.st == MST) { mp.st = 0; mp.ph ^= 1; }
  }
  tail();
  wg_wait<0>();
  fence_acc(acc);
  if (leader) release(prev);
}

__global__ void __cluster_dims__(2, 1, 1) __launch_bounds__(384, 1)
mega_kernel(const __grid_constant__ CUtensorMap tW1, const __grid_constant__ CUtensorMap tW2,
            const __grid_constant__ CUtensorMap tWqkv, const __grid_constant__ CUtensorMap tWo,
            const __grid_constant__ CUtensorMap tH, const __grid_constant__ CUtensorMap tXn, const Params p) {
  extern __shared__ __align__(1024) uint8_t smem_raw[];
  const uint32_t smem = smem_u32(smem_raw);
  if (smem & 1023) __trap();
  Bars* bars = reinterpret_cast<Bars*>(smem_raw + BARS_OFF);
  const int tid = threadIdx.x, warp = tid >> 5, lane = tid & 31, cta = blockIdx.x;
  const bool is_g1 = cta < N_G1, is_g2 = cta < N_G2;
  const int g1_t = 2 * ((cta >> 1) / 3) + (cta & 1), g1_j = (cta >> 1) % 3;
  const int g1_rot = (5 * (g1_t >> 1)) & 31;
  const int pair = cta >> 1, g2_h = pair & 1, g2_j = (pair >> 1) % 3, g2_i = 2 * (pair / 6) + (cta & 1);

  const int fpart = cta >> 5, fgrp = (cta >> 2) & 7, fkq = cta & 3;
  const uint32_t ftile = smem + FOLD_OFF;
  const uint32_t stg_xn = smem + M_A, stg_h = smem + M_STAGE + M_A;

  if (warp >= 8) {
    reg_dealloc<72>();
    if (warp == 8) {
      if (lane == 0) {
        for (int s = 0; s < MST; s++) { mbar_init(smem_u32(&bars->full[s]), 1); mbar_init(smem_u32(&bars->empty[s]), 4); }
        for (int s = 0; s < FST; s++) { mbar_init(smem_u32(&bars->ffull[s]), 1); mbar_init(smem_u32(&bars->fempty[s]), 1); }
        for (int w = 0; w < 2; w++) {
          mbar_init(smem_u32(&bars->xbar[w]), 1);
          mbar_init(smem_u32(&bars->jfull[w]), 1);
          mbar_init(smem_u32(&bars->jack[w]), 2);
          mbar_init(smem_u32(&bars->efull[w]), 1);
          mbar_init(smem_u32(&bars->jend[w]), 1);
        }
        mbar_init(smem_u32(&bars->stg_done), 4);
        mbar_init(smem_u32(&bars->xsent[0]), 1); mbar_init(smem_u32(&bars->xsent[1]), 1);
        mbar_init(smem_u32(&bars->p0bar), 1);
        mbar_init(smem_u32(&bars->lnpub), 2);
        mbar_init(smem_u32(&bars->peer_done), 2);
        asm volatile("fence.mbarrier_init.release.cluster;" ::: "memory");
        PROF(1, 24);
        if (cta < 128) {
          mbar_expect_tx(smem_u32(&bars->p0bar), FOLD_TILE + FOLD_PHI);
          bulk_load(ftile + FOLD_TILE, p.wphi + fgrp * 4 * 324, FOLD_PHI, smem_u32(&bars->p0bar));
          if (fpart < 3) tma2d(ftile, &tWqkv, fpart * DM + fgrp * 72, fkq * 144, smem_u32(&bars->p0bar));
          else tma2d(ftile, &tWo, fgrp * 72, fkq * 144, smem_u32(&bars->p0bar));
        }
        if (is_g1) {
#pragma unroll 1
          for (int s = 0; s < MST; s++) {
            mbar_expect_tx(smem_u32(&bars->full[s]), M_STAGE);
            tma3d_prefetch(&tW1, 0, ((s + g1_rot) & 31) * 64, g1_t * 2);
          }
        }
      }
      __syncwarp();
      named_arrive(8, 320);
    }
    asm volatile("barrier.cluster.arrive.relaxed.aligned;" ::: "memory");
    if (warp == 10) named_bar(8, 320);
    if (warp == 10 && cta < 128) {
      named_bar(3, 288);
      if (lane == 0) {
        tma4d_store(&tH, 0, (cta * 16) & 63, 0, cta >> 2, stg_h);
        tma4d_store(&tXn, 0, (cta * 16) & 127, 0, cta >> 3, stg_xn);
        asm volatile("cp.async.bulk.commit_group;" ::: "memory");
        bulk_wait_all();
        PROF(2, 7);
        flag_add_after_bulk(cnt_ptr(C_LNK + (cta >> 2)));
        asm volatile("red.relaxed.gpu.global.add.u32 [%0], 1;" ::"l"(cnt_ptr(C_LN)) : "memory");
        PROF(1, 11);
        if (is_g1) {
#pragma unroll 1
          for (int s = 0; s < MST; s++) tma3d(smem + s * M_STAGE, &tW1, 0, ((s + g1_rot) & 31) * 64, g1_t * 2, smem_u32(&bars->full[s]));
        }
      }
      __syncwarp();
    }
    if (warp == 11) { named_bar(4, 288); if (lane == 0) { flag_add(cnt_ptr(C_FOLD)); PROF(1, 13); } }
    __syncwarp();
    asm volatile("barrier.cluster.wait.acquire.aligned;" ::: "memory");
    if (warp == 10 && lane == 0 && is_g1) {
      mbar_arrive(smem_u32(&bars->lnpub));
      mbar_arrive_peer(mapa(smem_u32(&bars->lnpub), (cta & 1) ^ 1));
    }
    const uint32_t hoff = (cta & 1) * (M_B / 2);
    const uint8_t* hsrc = g_h_img + (size_t)g1_j * 24576 + hoff;
    if (warp == 8 && lane < MST && is_g1) {
      const int kb = (lane + g1_rot) & 31;
      if (lane == 0) PROF(2, 3);
      flag_wait(cnt_ptr(C_LNK + kb), 4);
      if (lane == 0) PROF(2, 4);
      if (lane < 2) mbar_wait(smem_u32(&bars->lnpub), 0);
      fence_proxy_async_global();
      if (lane == 0) PROF(2, 0);
      bulk_load_mc(smem + lane * M_STAGE + M_A + hoff, hsrc + (size_t)kb * 3 * 24576, M_B / 2, smem_u32(&bars->full[lane]), 3);
    }
    __syncwarp();
    if (warp == 8 && lane == 0 && is_g1) {
      const uint32_t full0 = smem_u32(&bars->full[0]), empty0 = smem_u32(&bars->empty[0]);
      flag_wait(cnt_ptr(C_LN), 128);
      fence_proxy_async_global();
      int st = 0; uint32_t ph = 0;
#pragma unroll 1
      for (int it = MST; it < 32; it++) {
        const int kb = (it + g1_rot) & 31;
        mbar_wait(empty0 + 8 * st, ph);
        const uint32_t fb = full0 + 8 * st, dst = smem + st * M_STAGE;
        mbar_expect_tx(fb, M_STAGE);
        tma3d(dst, &tW1, 0, kb * 64, g1_t * 2, fb);
        bulk_load_mc(dst + M_A + hoff, hsrc + (size_t)kb * 3 * 24576, M_B / 2, fb, 3);
        if (++st == MST) { st = 0; ph ^= 1; }
      }
      if (is_g2) {
        const uint8_t* usrc = g_u_img + (size_t)g2_j * 72 * 24576 + hoff;
#pragma unroll 1
        for (int m = 0; m < 36; m++) {
          const int kb = 36 * g2_h + (m < 18 ? 2 * m : 2 * (m - 18) + 1);
          mbar_wait(empty0 + 8 * st, ph);
          const uint32_t fb = full0 + 8 * st, dst = smem + st * M_STAGE;
          mbar_expect_tx(fb, M_STAGE);
          tma3d(dst, &tW2, 0, kb * 64, g2_i * 2, fb);
          if (m >= MST) {
            if (m == 18) { flag_wait(cnt_ptr(C_U + (g2_j * 2 + g2_h) * 2 + 1), 18); fence_proxy_async_global(); }
            bulk_load_mc(dst + M_A + hoff, usrc + (size_t)kb * 24576, M_B / 2, fb, 3);
          } else if (m == MST - 1) {
            mbar_wait(smem_u32(&bars->stg_done), 0);
            flag_wait(cnt_ptr(C_U + (g2_j * 2 + g2_h) * 2 + 0), 18);
            fence_proxy_async_global();
            PROF(2, 1);
            int s2 = st + 1;
#pragma unroll 1
            for (int mm = 0; mm < MST; mm++) {
              if (s2 == MST) s2 = 0;
              bulk_load_mc(smem + s2 * M_STAGE + M_A + hoff, usrc + (size_t)(36 * g2_h + 2 * mm) * 24576, M_B / 2, full0 + 8 * s2, 3);
              s2++;
            }
          }
          if (++st == MST) { st = 0; ph ^= 1; }
        }
        const uint8_t* osrc = g_o_img + (size_t)g2_i * 9 * 16384;
        const uint8_t* wsrc = g_wo_img + (size_t)(2 * g2_j + g2_h) * 9 * 12288;
#pragma unroll 1
        for (int m = 0; m < 9; m++) {
          if (m < 8 && !(m & 1)) {
            flag_wait(cnt_ptr(C_O + g2_i * 4 + (m >> 1)), 1);
            fence_proxy_async_global();
            if (m == 6) PROF(2, 2);
          }
          mbar_wait(empty0 + 8 * st, ph);
          const uint32_t fb = full0 + 8 * st, dst = smem + st * M_STAGE;
          mbar_expect_tx(fb, 16384 + 12288);
          bulk_load(dst, osrc + m * 16384, 16384, fb);
          bulk_load(dst + M_A, wsrc + m * 12288, 12288, fb);
          if (++st == MST) { st = 0; ph ^= 1; }
        }
      }
    }
    if (!is_g2) {
      if (lane == 0) {
        if (warp == 8) {
          if (is_g1) { mbar_wait(smem_u32(&bars->stg_done), 0); mbar_wait(smem_u32(&bars->peer_done), 0); }
          f_producer(bars, smem);
        } else if (warp >= 10) f_helper(bars, smem, warp - 10);
      }
      if (warp == 9 && !is_g1) kvb_finalize(cta - N_G1, lane);
    } else if (warp > 8) {
      if (warp < 11 && lane == 0) {
        const int w = warp - 9;
        const uint32_t b0 = smem + (w == 0 ? FOLD_OFF : 3 * M_STAGE + 28672), b1 = smem + (w == 0 ? FOLD_OFF + 12288 : 4 * M_STAGE + 28672);
        mbar_wait(smem_u32(&bars->xsent[w]), 0);
        uint8_t* mine = g_xch + (size_t)(cta * 2 + w) * 24576;
        bulk_store(mine, b0, 12288);
        bulk_store(mine + 12288, b1, 12288);
        bulk_wait_all();
        FLAG_X(cnt_ptr(C_X + cta * 2 + w));
        flag_wait(cnt_ptr(C_X + (cta ^ 2) * 2 + w), 1);
        fence_proxy_async_global();
        const uint8_t* theirs = g_xch + (size_t)((cta ^ 2) * 2 + w) * 24576;
        const uint32_t xb = smem_u32(&bars->xbar[w]);
        mbar_expect_tx(xb, 24576);
        bulk_load(b0, theirs, 12288, xb);
        bulk_load(b1, theirs + 12288, 12288, xb);
      }
    }
    __syncwarp();
    role_done(lane);
  } else {
    if (tid == 0) PROF(0, 0);
    {
      uint32_t raw[2][9];
      if (cta < 128) {
#pragma unroll
        for (int r = 0; r < 2; r++)
#pragma unroll
          for (int c = 0; c < 9; c++)
            raw[r][c] = __ldg(reinterpret_cast<const uint32_t*>(p.x + (size_t)(cta * 16 + warp * 2 + r) * DM + c * 64) + lane);
      }
      asm volatile("barrier.cluster.arrive.relaxed.aligned;" ::: "memory");
      if (cta < 128) {
        p0_layernorm(raw, stg_xn, stg_h, warp, lane);
        fence_proxy_async_smem();
        named_arrive(3, 288);
        if (tid == 0) PROF(0, 1);
        uint32_t fa[9];
        named_bar(8, 320);
        mbar_wait(smem_u32(&bars->p0bar), 0);
        if (tid == 0) PROF(1, 22);
        p0_fold_a(ftile + FOLD_TILE + (warp >> 1) * 648, fpart, lane, fa);
        p0_fold(fpart, 4 * fgrp + (warp >> 1), fkq, warp, lane, ftile, fa);
        if (tid == 0) PROF(1, 12);
      } else {
        uint4* z = reinterpret_cast<uint4*>(g_kvsum);
        for (int i = (cta - 128) * 256 + tid; i < 32 * 36 * 5; i += 1024) z[i] = make_uint4(0u, 0u, 0u, 0u);
        named_bar(8, 320);
      }
      named_arrive(4, 288);
      asm volatile("barrier.cluster.wait.acquire.aligned;" ::: "memory");
    }
    reg_alloc<216>();
    const int wg = warp >> 2, w4 = warp & 3;
    const bool leader = (w4 == 0 && lane == 0);
    const int g = lane >> 2, j = lane & 3;
    if (is_g1) {
      MainPos mp{0, 0};
      float acc[96];
      const uint32_t peer_empty0 = mapa(smem_u32(&bars->empty[0]), (cta & 1) ^ 1);
      {
        const int f0 = g1_t * 128 + wg * 64 + w4 * 16 + g;
        const float hb0 = 0.5f * __bfloat162float(p.b1[f0]), hb1 = 0.5f * __bfloat162float(p.b1[f0 + 8]);
#pragma unroll
        for (int b = 0; b < 24; b++) { acc[4 * b] = hb0; acc[4 * b + 1] = hb0; acc[4 * b + 2] = hb1; acc[4 * b + 3] = hb1; }
      }
      main_loop<32, false>(acc, smem, bars, mp, wg, leader, peer_empty0, []() {});
      if (leader && !is_g2) mbar_arrive_peer(mapa(smem_u32(&bars->peer_done), (cta & 1) ^ 1));
      if (tid == 0) { PROF(0, 2); CPROF(2, 24); }
      {
        named_bar(6, 256);
        if (wg == 1) named_bar(7, 256);
        if (tid == 0) PROF(1, 14);
        const uint32_t stg = smem + (2 + wg) * M_STAGE + M_A;
        const int mi = lane >> 3;
        const int srow = w4 * 16 + (mi & 1) * 8 + (lane & 7);
        const int kb = 2 * g1_t + wg;
        uint8_t* udst = g_u_img + ((size_t)g1_j * 72 + kb) * 24576;
#pragma unroll
        for (int b = 0; b < 24; b += 2) {
          uint32_t r[4];
#pragma unroll
          for (int q = 0; q < 4; q++) {
            const int idx = 4 * (b + (q >> 1)) + 2 * (q & 1);
            float o[2];
#pragma unroll
            for (int e = 0; e < 2; e++) {
              const float w = acc[idx + e];
              const float t = tanh_f(w * fmaf(w * w, 8.f * 0.044715f * 0.7978845608028654f, 2.f * 0.7978845608028654f));
              o[e] = fmaf(w, t, w);
            }
            r[q] = pack2(o[0], o[1]);
          }
          const int blk = b + (mi >> 1);
          stmatrix_x4(stg + (blk >> 3) * 8192 + srow * 128 + (((blk & 7) ^ (srow & 7)) << 4), r[0], r[1], r[2], r[3]);
          if (b == 22 && wg == 0) named_arrive(7, 256);
          if ((b & 7) == 6) {
            fence_proxy_async_smem();
            named_bar(1 + wg, 128);
            if (leader) bulk_store(udst + (b >> 3) * 8192, stg + (b >> 3) * 8192, 8192);
          }
        }
        if (tid == 0) PROF(1, 15);
        if (leader) {
          bulk_wait_all();
          if (tid == 0) PROF(1, 17);
          mbar_arrive(smem_u32(&bars->stg_done));
          mbar_arrive_peer(mapa(smem_u32(&bars->stg_done), (cta & 1) ^ 1));
          FLAG_U(cnt_ptr(C_U + (g1_j * 2 + kb / 36) * 2 + wg));
          if (wg == 0) PROF(0, 3);
        }
        __syncwarp();
      }
      if (is_g2) {
        const int r0 = g2_i * 128 + wg * 64 + w4 * 16 + g;
        const int c0 = g2_j * 192 + g2_h * 96 + 4 * j;
        main_loop<36, true>(acc, smem, bars, mp, wg, leader, peer_empty0, []() {});
        if (tid == 0) { PROF(0, 4); CPROF(2, 25); }
        const int t128 = w4 * 32 + lane;
        const uint32_t inb0 = smem + (wg == 0 ? FOLD_OFF : 3 * M_STAGE + 28672) + t128 * 16;
        const uint32_t inb1 = smem + (wg == 0 ? FOLD_OFF + 12288 : 4 * M_STAGE + 28672) + t128 * 16;
        named_bar(6, 256);
        float yk[48];
#pragma unroll
        for (int bb = 0; bb < 12; bb++) {
          float v0, v1, v2, v3;
          if (g2_h == 0) { v0 = acc[48 + 4 * bb]; v1 = acc[48 + 4 * bb + 1]; v2 = acc[48 + 4 * bb + 2]; v3 = acc[48 + 4 * bb + 3]; }
          else { v0 = acc[4 * bb]; v1 = acc[4 * bb + 1]; v2 = acc[4 * bb + 2]; v3 = acc[4 * bb + 3]; }
          asm volatile("st.shared.v4.f32 [%0], {%1, %2, %3, %4};" ::"r"((bb < 6 ? inb0 : inb1) + (bb % 6) * 2048), "f"(v0), "f"(v1), "f"(v2), "f"(v3) : "memory");
        }
#pragma unroll
        for (int i = 0; i < 48; i++) yk[i] = g2_h == 0 ? acc[i] : acc[48 + i];
        fence_proxy_async_smem();
        named_bar(1 + wg, 128);
        if (leader) mbar_arrive(smem_u32(&bars->xsent[wg]));
        if (tid == 0) PROF(1, 18);
        uint2 xv[6][2];
#pragma unroll
        for (int m = 0; m < 6; m++) {
          xv[m][0] = __ldg(reinterpret_cast<const uint2*>(p.x + (size_t)r0 * DM + c0 + 16 * m));
          xv[m][1] = __ldg(reinterpret_cast<const uint2*>(p.x + (size_t)(r0 + 8) * DM + c0 + 16 * m));
        }
        const float bias2a = __bfloat162float(p.b2[r0]), bias2b = __bfloat162float(p.b2[r0 + 8]);
        float sacc[48];
        {
          const uint32_t full0 = smem_u32(&bars->full[0]), empty0 = smem_u32(&bars->empty[0]);
          int prev = 0;
#pragma unroll 1
          for (int m = 0; m < 9; m++) {
            mbar_wait(full0 + 8 * mp.st, mp.ph);
            const uint32_t sA = smem + mp.st * M_STAGE + wg * 8192, sB = smem + mp.st * M_STAGE + M_A;
            if (m == 0) {
              wg_arrive();
#pragma unroll
              for (int k = 0; k < 4; k++)
                WgmmaSS<96, 0, 0>::mma(sacc, make_desc(sA + k * 32, 16, 1024, 1), make_desc(sB + k * 32, 16, 1024, 1), k > 0);
              wg_commit();
              fence_acc(sacc);
            } else {
              fence_acc(sacc);
              wg_arrive();
#pragma unroll
              for (int k = 0; k < 4; k++)
                WgmmaSS<96, 0, 0>::mma(sacc, make_desc(sA + k * 32, 16, 1024, 1), make_desc(sB + k * 32, 16, 1024, 1), 1);
              wg_commit();
              fence_acc(sacc);
              wg_wait<1>();
              if (leader) mbar_arrive_n(empty0 + 8 * prev, 2);
            }
            prev = mp.st;
            if (++mp.st == MST) { mp.st = 0; mp.ph ^= 1; }
          }
          wg_wait<0>();
          fence_acc(sacc);
        }
        if (tid == 0) PROF(1, 20);
        mbar_wait(smem_u32(&bars->xbar[wg]), 0);
        if (tid == 0) PROF(1, 19);
#pragma unroll
        for (int m = 0; m < 6; m++) {
          uint32_t res[2][2];
#pragma unroll
          for (int h2 = 0; h2 < 2; h2++) {
            const int bb = 2 * m + h2;
            float4 o;
            asm volatile("ld.shared.v4.f32 {%0, %1, %2, %3}, [%4];" : "=f"(o.x), "=f"(o.y), "=f"(o.z), "=f"(o.w) : "r"((bb < 6 ? inb0 : inb1) + (bb % 6) * 2048) : "memory");
            const float y[4] = {yk[4 * bb] + o.x + bias2a, yk[4 * bb + 1] + o.y + bias2a, yk[4 * bb + 2] + o.z + bias2b, yk[4 * bb + 3] + o.w + bias2b};
            const uint32_t x0 = h2 ? xv[m][0].y : xv[m][0].x, x1 = h2 ? xv[m][1].y : xv[m][1].x;
            const float xval[4] = {lo_f(x0), hi_f(x0), lo_f(x1), hi_f(x1)};
            float rr[4];
#pragma unroll
            for (int e = 0; e < 4; e++) {
              const float hy = 0.5f * y[e];
              const float gate = fmaf(hy, tanh_f(hy), hy);
              rr[e] = fmaf(sacc[4 * bb + e], gate, xval[e]);
            }
            res[0][h2] = pack2(rr[0], rr[1]); res[1][h2] = pack2(rr[2], rr[3]);
          }
          *reinterpret_cast<uint2*>(p.out + (size_t)r0 * DM + c0 + 16 * m) = make_uint2(res[0][0], res[0][1]);
          *reinterpret_cast<uint2*>(p.out + (size_t)(r0 + 8) * DM + c0 + 16 * m) = make_uint2(res[1][0], res[1][1]);
        }
        if (tid == 0) PROF(0, 5);
      }
    }
    if (!is_g2) {
      f_consumer(bars, smem, wg, w4, lane);
      if (leader) PROF(wg, 6);
    }
  }
}

typedef CUresult (*EncodeTiledFn)(CUtensorMap*, CUtensorMapDataType, cuuint32_t, void*, const cuuint64_t*, const cuuint64_t*,
                                  const cuuint32_t*, const cuuint32_t*, CUtensorMapInterleave, CUtensorMapSwizzle,
                                  CUtensorMapL2promotion, CUtensorMapFloatOOBfill);

static bool make_map(EncodeTiledFn fn, CUtensorMap* m, const void* ptr, int rank, const cuuint64_t* dims, const cuuint64_t* strides,
                     const cuuint32_t* box, CUtensorMapSwizzle sw) {
  cuuint32_t es[4] = {1, 1, 1, 1};
  return fn(m, CU_TENSOR_MAP_DATA_TYPE_BFLOAT16, rank, const_cast<void*>(ptr), dims, strides, box, es, CU_TENSOR_MAP_INTERLEAVE_NONE, sw,
            CU_TENSOR_MAP_L2_PROMOTION_L2_256B, CU_TENSOR_MAP_FLOAT_OOB_FILL_NONE) == CUDA_SUCCESS;
}

}

extern "C" void kernel_launch(void* const* d_in, const int* in_sizes, int n_in, void* d_out, int out_size) {
  using namespace hk;
  (void)in_sizes; (void)n_in; (void)out_size;
  static EncodeTiledFn fn = nullptr;
  static uint8_t* scratch = nullptr;
  if (!fn) {
    cudaGetSymbolAddress(reinterpret_cast<void**>(&scratch), g_scratch);
    void* f = nullptr;
    cudaDriverEntryPointQueryResult q;
    cudaGetDriverEntryPoint("cuTensorMapEncodeTiled", &f, cudaEnableDefault, &q);
    fn = (EncodeTiledFn)f;
    cudaFuncSetAttribute(mega_kernel, cudaFuncAttributeMaxDynamicSharedMemorySize, SMEM_BYTES);
  }
  CUtensorMap tW1, tW2, tWqkv, tWo, tH, tXn;
  {
    const cuuint64_t d1[3] = {64, SEQ, FF / 64}, s1[2] = {FF * 2, 128}, d2[3] = {64, FF, SEQ / 64}, s2[2] = {SEQ * 2, 128};
    const cuuint32_t b3[3] = {64, 64, 2};
    make_map(fn, &tW1, d_in[5], 3, d1, s1, b3, CU_TENSOR_MAP_SWIZZLE_128B);
    make_map(fn, &tW2, d_in[7], 3, d2, s2, b3, CU_TENSOR_MAP_SWIZZLE_128B);
    const cuuint64_t dq[2] = {3 * DM, DM}, sq[1] = {3 * DM * 2}, dw[2] = {DM, DM}, sw[1] = {DM * 2};
    const cuuint32_t b2[2] = {72, 144};
    make_map(fn, &tWqkv, d_in[1], 2, dq, sq, b2, CU_TENSOR_MAP_SWIZZLE_NONE);
    make_map(fn, &tWo, d_in[3], 2, dw, sw, b2, CU_TENSOR_MAP_SWIZZLE_NONE);
    const cuuint64_t dh[4] = {64, 64, 9, 32}, sh[3] = {128, 8192, 73728}, dx[4] = {64, 128, 9, 16}, sx[3] = {128, 16384, 147456};
    const cuuint32_t b4[4] = {64, 16, 9, 1};
    make_map(fn, &tH, scratch + O_H, 4, dh, sh, b4, CU_TENSOR_MAP_SWIZZLE_NONE);
    make_map(fn, &tXn, scratch + O_XN, 4, dx, sx, b4, CU_TENSOR_MAP_SWIZZLE_NONE);
  }
  Params p;
  p.x = (const bf16*)d_in[0]; p.wqkv = (const bf16*)d_in[1]; p.wphi = (const bf16*)d_in[2]; p.wo = (const bf16*)d_in[3];
  p.b1 = (const bf16*)d_in[6]; p.b2 = (const bf16*)d_in[8]; p.out = (bf16*)d_out;
  mega_kernel<<<NCTA, 384, SMEM_BYTES>>>(tW1, tW2, tWqkv, tWo, tH, tXn, p);
}
```
